```python
import torch

def _softmax(x, axis=-1):
    return torch.softmax(x, dim=axis)
def _gelu(x):
    return torch.nn.functional.gelu(x, approximate="tanh")
def _silu(x):
    return torch.nn.functional.silu(x)
def _sigmoid(x):
    return torch.sigmoid(x)
def _layernorm(x, axis=-1, eps=1e-5):
    m = x.mean(dim=axis, keepdim=True)
    v = x.var(dim=axis, keepdim=True, unbiased=False)
    return (x - m) / torch.sqrt(v + eps)
def _scatter_add(tgt, idx, src, axis=0):
    return tgt.clone().index_add_(axis, idx, src)
def _segment_sum(src, seg, n):
    out = torch.zeros((n,) + src.shape[1:], dtype=src.dtype)
    return out.index_add_(0, seg, src)
def _pad(x, pw):
    flat = tuple(v for pair in reversed(pw) for v in pair)
    return torch.nn.functional.pad(x, flat)

kernel_name = 'sequential_preLN__softmax_full_mha__swiglu_ffn__prompt'

def setup_inputs():

    _w = (lambda a: (lambda t: t.to(torch.bfloat16) if t.is_floating_point() else t)(torch.as_tensor(a)))
    def _A_setup():
        B, S, D = 1, 2048, 640
        return {
            "x": _w((lambda *s: torch.randn(*s, dtype=torch.bfloat16) * 0.05)(B, S, D)),
            "wqkv": _w((lambda *s: torch.randn(*s, dtype=torch.bfloat16) * 0.05)(D, 3 * D)),
            "wo": _w((lambda *s: torch.randn(*s, dtype=torch.bfloat16) * 0.05)(D, D)),
        }
    _A_in = _A_setup()

    def _B_setup():
        B, S, D, F = 1, 2048, 640, 1536
        return {
            "x": _w((lambda *s: torch.randn(*s, dtype=torch.bfloat16) * 0.05)(B, S, D)),
            "w_gate": _w((lambda *s: torch.randn(*s, dtype=torch.bfloat16) * 0.05)(D, F)),
            "w_up": _w((lambda *s: torch.randn(*s, dtype=torch.bfloat16) * 0.05)(D, F)),
            "w_down": _w((lambda *s: torch.randn(*s, dtype=torch.bfloat16) * 0.05)(F, D)),
        }
    _B_in = _B_setup()

    return {
        "A_x": _A_in["x"],
        "A_wqkv": _A_in["wqkv"],
        "A_wo": _A_in["wo"],
        "B_x": _B_in["x"],
        "B_w_gate": _B_in["w_gate"],
        "B_w_up": _B_in["w_up"],
        "B_w_down": _B_in["w_down"],
    }

def reference(A_x, A_wqkv, A_wo, B_x, B_w_gate, B_w_up, B_w_down):
    def _A_ref(x, wqkv, wo):
        B, S, D = x.shape
        H = 32; Dh = D // H
        qkv = (lambda x, *d: x.permute(*d))((x @ wqkv).reshape(B, S, 3, H, Dh), 2, 0, 3, 1, 4)
        q, k, v = qkv[0], qkv[1], qkv[2]
        scale = Dh ** -0.5
        scores = torch.einsum("bhqd,bhkd->bhqk", q, k) * scale
        p = _softmax(scores, axis=-1)
        o = torch.einsum("bhqk,bhkd->bhqd", p, v)
        return (lambda x, *d: x.permute(*d))(o, 0, 2, 1, 3).reshape(B, S, D) @ wo

    def _B_ref(x, w_gate, w_up, w_down):
        g = _silu(x @ w_gate)
        u = x @ w_up
        return (g * u) @ w_down

    x = A_x
    h = x + _A_ref(_layernorm(x, axis=-1), A_wqkv, A_wo)
    h2 = h + _B_ref(_layernorm(h, axis=-1), B_w_gate, B_w_up, B_w_down)
    return h2
```

```cpp
#include <cuda_runtime.h>
#include <cuda_bf16.h>
#include <cuda.h>
#include <stdint.h>

typedef __nv_bfloat16 bf16;

constexpr int SEQ = 2048, DM = 640, NH = 32, DH = 20, FF = 1536;

__device__ __align__(1024) bf16 g_qkv[3 * NH * SEQ * 32];
__device__ __align__(1024) bf16 g_o[SEQ * DM];
__device__ __align__(1024) bf16 g_h[SEQ * DM];
__device__ __align__(1024) bf16 g_act[SEQ * FF];

__device__ __forceinline__ uint32_t smem_u32(const void* p) { return (uint32_t)__cvta_generic_to_shared(p); }
__device__ __forceinline__ void mbar_init(uint32_t bar, uint32_t count) {
  asm volatile("mbarrier.init.shared::cta.b64 [%0], %1;" :: "r"(bar), "r"(count) : "memory");
}
__device__ __forceinline__ void mbar_expect_tx(uint32_t bar, uint32_t bytes) {
  asm volatile("mbarrier.arrive.expect_tx.shared::cta.b64 _, [%0], %1;" :: "r"(bar), "r"(bytes) : "memory");
}
__device__ __forceinline__ void mbar_arrive(uint32_t bar) {
  asm volatile("mbarrier.arrive.shared::cta.b64 _, [%0];" :: "r"(bar) : "memory");
}
__device__ __forceinline__ void mbar_wait(uint32_t bar, uint32_t parity) {
  uint32_t done;
  uint32_t it = 0;
  do {
    asm volatile("{\n.reg .pred p;\nmbarrier.try_wait.parity.shared::cta.b64 p, [%1], %2;\nselp.u32 %0, 1, 0, p;\n}"
                 : "=r"(done) : "r"(bar), "r"(parity) : "memory");
    if (++it > 4000000u) __trap();
  } while (!done);
}
__device__ __forceinline__ void tma_load_2d(uint32_t dst, const CUtensorMap* map, int c0, int c1, uint32_t bar) {
  asm volatile("cp.async.bulk.tensor.2d.shared::cluster.global.mbarrier::complete_tx::bytes [%0], [%1, {%3, %4}], [%2];"
               :: "r"(dst), "l"((uint64_t)map), "r"(bar), "r"(c0), "r"(c1) : "memory");
}
__device__ __forceinline__ void fence_async_smem() { asm volatile("fence.proxy.async.shared::cta;" ::: "memory"); }
__device__ __forceinline__ void wg_fence() { asm volatile("wgmma.fence.sync.aligned;" ::: "memory"); }
__device__ __forceinline__ void wg_commit() { asm volatile("wgmma.commit_group.sync.aligned;" ::: "memory"); }
template <int N> __device__ __forceinline__ void wg_wait() { asm volatile("wgmma.wait_group.sync.aligned %0;" :: "n"(N) : "memory"); }
template <int N> __device__ __forceinline__ void reg_fence(float (&d)[N]) {
#pragma unroll
  for (int i = 0; i < N; i++) asm volatile("" : "+f"(d[i]) :: "memory");
}
__device__ __forceinline__ uint64_t make_desc(uint32_t addr, uint32_t lbo, uint32_t sbo, uint32_t swz) {
  return (uint64_t)((addr & 0x3FFFF) >> 4) | ((uint64_t)(lbo >> 4) << 16) | ((uint64_t)(sbo >> 4) << 32) | ((uint64_t)swz << 62);
}
__device__ __forceinline__ uint32_t pack_bf16(float a, float b) {
  __nv_bfloat162 v = __floats2bfloat162_rn(a, b);
  return *reinterpret_cast<uint32_t*>(&v);
}
__device__ __forceinline__ void named_bar_sync(int id, int n) { asm volatile("bar.sync %0, %1;" :: "r"(id), "r"(n) : "memory"); }

template<int TB> __device__ __forceinline__ void wgmma_ss_n240(float (&d)[120], uint64_t descA, uint64_t descB, int scaleD) {
  asm volatile("{\n.reg .pred p;\nsetp.ne.b32 p, %122, 0;\n"
    "wgmma.mma_async.sync.aligned.m64n240k16.f32.bf16.bf16 {%0, %1, %2, %3, %4, %5, %6, %7, %8, %9, %10, %11, %12, %13, %14, %15, %16, %17, %18, %19, %20, %21, %22, %23, %24, %25, %26, %27, %28, %29, %30, %31, %32, %33, %34, %35, %36, %37, %38, %39, %40, %41, %42, %43, %44, %45, %46, %47, %48, %49, %50, %51, %52, %53, %54, %55, %56, %57, %58, %59, %60, %61, %62, %63, %64, %65, %66, %67, %68, %69, %70, %71, %72, %73, %74, %75, %76, %77, %78, %79, %80, %81, %82, %83, %84, %85, %86, %87, %88, %89, %90, %91, %92, %93, %94, %95, %96, %97, %98, %99, %100, %101, %102, %103, %104, %105, %106, %107, %108, %109, %110, %111, %112, %113, %114, %115, %116, %117, %118, %119}, %120, %121, p, 1, 1, 0, %123;\n}"
    : "+f"(d[0]), "+f"(d[1]), "+f"(d[2]), "+f"(d[3]), "+f"(d[4]), "+f"(d[5]), "+f"(d[6]), "+f"(d[7]), "+f"(d[8]), "+f"(d[9]), "+f"(d[10]), "+f"(d[11]), "+f"(d[12]), "+f"(d[13]), "+f"(d[14]), "+f"(d[15]), "+f"(d[16]), "+f"(d[17]), "+f"(d[18]), "+f"(d[19]), "+f"(d[20]), "+f"(d[21]), "+f"(d[22]), "+f"(d[23]), "+f"(d[24]), "+f"(d[25]), "+f"(d[26]), "+f"(d[27]), "+f"(d[28]), "+f"(d[29]), "+f"(d[30]), "+f"(d[31]), "+f"(d[32]), "+f"(d[33]), "+f"(d[34]), "+f"(d[35]), "+f"(d[36]), "+f"(d[37]), "+f"(d[38]), "+f"(d[39]), "+f"(d[40]), "+f"(d[41]), "+f"(d[42]), "+f"(d[43]), "+f"(d[44]), "+f"(d[45]), "+f"(d[46]), "+f"(d[47]), "+f"(d[48]), "+f"(d[49]), "+f"(d[50]), "+f"(d[51]), "+f"(d[52]), "+f"(d[53]), "+f"(d[54]), "+f"(d[55]), "+f"(d[56]), "+f"(d[57]), "+f"(d[58]), "+f"(d[59]), "+f"(d[60]), "+f"(d[61]), "+f"(d[62]), "+f"(d[63]), "+f"(d[64]), "+f"(d[65]), "+f"(d[66]), "+f"(d[67]), "+f"(d[68]), "+f"(d[69]), "+f"(d[70]), "+f"(d[71]), "+f"(d[72]), "+f"(d[73]), "+f"(d[74]), "+f"(d[75]), "+f"(d[76]), "+f"(d[77]), "+f"(d[78]), "+f"(d[79]), "+f"(d[80]), "+f"(d[81]), "+f"(d[82]), "+f"(d[83]), "+f"(d[84]), "+f"(d[85]), "+f"(d[86]), "+f"(d[87]), "+f"(d[88]), "+f"(d[89]), "+f"(d[90]), "+f"(d[91]), "+f"(d[92]), "+f"(d[93]), "+f"(d[94]), "+f"(d[95]), "+f"(d[96]), "+f"(d[97]), "+f"(d[98]), "+f"(d[99]), "+f"(d[100]), "+f"(d[101]), "+f"(d[102]), "+f"(d[103]), "+f"(d[104]), "+f"(d[105]), "+f"(d[106]), "+f"(d[107]), "+f"(d[108]), "+f"(d[109]), "+f"(d[110]), "+f"(d[111]), "+f"(d[112]), "+f"(d[113]), "+f"(d[114]), "+f"(d[115]), "+f"(d[116]), "+f"(d[117]), "+f"(d[118]), "+f"(d[119])
    : "l"(descA), "l"(descB), "r"(scaleD), "n"(TB));
}
template<int TB> __device__ __forceinline__ void wgmma_ss_n128(float (&d)[64], uint64_t descA, uint64_t descB, int scaleD) {
  asm volatile("{\n.reg .pred p;\nsetp.ne.b32 p, %66, 0;\n"
    "wgmma.mma_async.sync.aligned.m64n128k16.f32.bf16.bf16 {%0, %1, %2, %3, %4, %5, %6, %7, %8, %9, %10, %11, %12, %13, %14, %15, %16, %17, %18, %19, %20, %21, %22, %23, %24, %25, %26, %27, %28, %29, %30, %31, %32, %33, %34, %35, %36, %37, %38, %39, %40, %41, %42, %43, %44, %45, %46, %47, %48, %49, %50, %51, %52, %53, %54, %55, %56, %57, %58, %59, %60, %61, %62, %63}, %64, %65, p, 1, 1, 0, %67;\n}"
    : "+f"(d[0]), "+f"(d[1]), "+f"(d[2]), "+f"(d[3]), "+f"(d[4]), "+f"(d[5]), "+f"(d[6]), "+f"(d[7]), "+f"(d[8]), "+f"(d[9]), "+f"(d[10]), "+f"(d[11]), "+f"(d[12]), "+f"(d[13]), "+f"(d[14]), "+f"(d[15]), "+f"(d[16]), "+f"(d[17]), "+f"(d[18]), "+f"(d[19]), "+f"(d[20]), "+f"(d[21]), "+f"(d[22]), "+f"(d[23]), "+f"(d[24]), "+f"(d[25]), "+f"(d[26]), "+f"(d[27]), "+f"(d[28]), "+f"(d[29]), "+f"(d[30]), "+f"(d[31]), "+f"(d[32]), "+f"(d[33]), "+f"(d[34]), "+f"(d[35]), "+f"(d[36]), "+f"(d[37]), "+f"(d[38]), "+f"(d[39]), "+f"(d[40]), "+f"(d[41]), "+f"(d[42]), "+f"(d[43]), "+f"(d[44]), "+f"(d[45]), "+f"(d[46]), "+f"(d[47]), "+f"(d[48]), "+f"(d[49]), "+f"(d[50]), "+f"(d[51]), "+f"(d[52]), "+f"(d[53]), "+f"(d[54]), "+f"(d[55]), "+f"(d[56]), "+f"(d[57]), "+f"(d[58]), "+f"(d[59]), "+f"(d[60]), "+f"(d[61]), "+f"(d[62]), "+f"(d[63])
    : "l"(descA), "l"(descB), "r"(scaleD), "n"(TB));
}
template<int TB> __device__ __forceinline__ void wgmma_ss_n80(float (&d)[40], uint64_t descA, uint64_t descB, int scaleD) {
  asm volatile("{\n.reg .pred p;\nsetp.ne.b32 p, %42, 0;\n"
    "wgmma.mma_async.sync.aligned.m64n80k16.f32.bf16.bf16 {%0, %1, %2, %3, %4, %5, %6, %7, %8, %9, %10, %11, %12, %13, %14, %15, %16, %17, %18, %19, %20, %21, %22, %23, %24, %25, %26, %27, %28, %29, %30, %31, %32, %33, %34, %35, %36, %37, %38, %39}, %40, %41, p, 1, 1, 0, %43;\n}"
    : "+f"(d[0]), "+f"(d[1]), "+f"(d[2]), "+f"(d[3]), "+f"(d[4]), "+f"(d[5]), "+f"(d[6]), "+f"(d[7]), "+f"(d[8]), "+f"(d[9]), "+f"(d[10]), "+f"(d[11]), "+f"(d[12]), "+f"(d[13]), "+f"(d[14]), "+f"(d[15]), "+f"(d[16]), "+f"(d[17]), "+f"(d[18]), "+f"(d[19]), "+f"(d[20]), "+f"(d[21]), "+f"(d[22]), "+f"(d[23]), "+f"(d[24]), "+f"(d[25]), "+f"(d[26]), "+f"(d[27]), "+f"(d[28]), "+f"(d[29]), "+f"(d[30]), "+f"(d[31]), "+f"(d[32]), "+f"(d[33]), "+f"(d[34]), "+f"(d[35]), "+f"(d[36]), "+f"(d[37]), "+f"(d[38]), "+f"(d[39])
    : "l"(descA), "l"(descB), "r"(scaleD), "n"(TB));
}
template<int TB> __device__ __forceinline__ void wgmma_rs_n24(float (&d)[12], uint32_t a0, uint32_t a1, uint32_t a2, uint32_t a3, uint64_t descB, int scaleD) {
  asm volatile("{\n.reg .pred p;\nsetp.ne.b32 p, %17, 0;\n"
    "wgmma.mma_async.sync.aligned.m64n24k16.f32.bf16.bf16 {%0, %1, %2, %3, %4, %5, %6, %7, %8, %9, %10, %11}, {%12, %13, %14, %15}, %16, p, 1, 1, %18;\n}"
    : "+f"(d[0]), "+f"(d[1]), "+f"(d[2]), "+f"(d[3]), "+f"(d[4]), "+f"(d[5]), "+f"(d[6]), "+f"(d[7]), "+f"(d[8]), "+f"(d[9]), "+f"(d[10]), "+f"(d[11])
    : "r"(a0), "r"(a1), "r"(a2), "r"(a3), "l"(descB), "r"(scaleD), "n"(TB));
}


__device__ __forceinline__ void ln_prologue(const bf16* __restrict__ src, int row0, uint8_t* sA, int ctid) {
  const int warp = ctid >> 5, lane = ctid & 31;
  for (int rr = 0; rr < 16; rr += 2) {
    uint2 v[2][5];
#pragma unroll
    for (int u = 0; u < 2; u++) {
      const uint2* p = reinterpret_cast<const uint2*>(src + (size_t)(row0 + warp * 16 + rr + u) * DM);
#pragma unroll
      for (int j = 0; j < 5; j++) v[u][j] = p[lane + 32 * j];
    }
#pragma unroll
    for (int u = 0; u < 2; u++) {
      float f[20];
#pragma unroll
      for (int j = 0; j < 5; j++) {
        f[4 * j + 0] = __uint_as_float(v[u][j].x << 16);
        f[4 * j + 1] = __uint_as_float(v[u][j].x & 0xffff0000u);
        f[4 * j + 2] = __uint_as_float(v[u][j].y << 16);
        f[4 * j + 3] = __uint_as_float(v[u][j].y & 0xffff0000u);
      }
      float s = 0.f;
#pragma unroll
      for (int j = 0; j < 20; j++) s += f[j];
#pragma unroll
      for (int o = 16; o > 0; o >>= 1) s += __shfl_xor_sync(0xffffffffu, s, o);
      const float mean = s * (1.0f / DM);
      float q = 0.f;
#pragma unroll
      for (int j = 0; j < 20; j++) { f[j] -= mean; q += f[j] * f[j]; }
#pragma unroll
      for (int o = 16; o > 0; o >>= 1) q += __shfl_xor_sync(0xffffffffu, q, o);
      const float rstd = rsqrtf(q * (1.0f / DM) + 1e-5f);
      const int r = warp * 16 + rr + u;
#pragma unroll
      for (int j = 0; j < 5; j++) {
        const int e = (lane + 32 * j) * 4;
        const int kb = e >> 6;
        const int byte = (e & 63) * 2;
        const int chunk = byte >> 4;
        const int sw = ((chunk ^ (r & 7)) << 4) | (byte & 15);
        uint2 o;
        o.x = pack_bf16(f[4 * j + 0] * rstd, f[4 * j + 1] * rstd);
        o.y = pack_bf16(f[4 * j + 2] * rstd, f[4 * j + 3] * rstd);
        *reinterpret_cast<uint2*>(sA + kb * 16384 + r * 128 + sw) = o;
      }
    }
  }
}

constexpr int K1_STAGES = 4;
constexpr int K1_SMEM = 163840 + K1_STAGES * 16384 + 1024;
__global__ void __launch_bounds__(288, 1) k1_ln_qkv(const bf16* __restrict__ x, const __grid_constant__ CUtensorMap tmW) {
  extern __shared__ __align__(1024) uint8_t smem[];
  uint8_t* sA = smem;
  uint8_t* sB = smem + 163840;
  const uint32_t bar0 = smem_u32(smem + 163840 + K1_STAGES * 16384);
  const int tid = threadIdx.x;
  const int mblk = blockIdx.x >> 3, nblk = blockIdx.x & 7;
  if (tid == 0) {
    for (int s = 0; s < K1_STAGES; s++) { mbar_init(bar0 + 8 * s, 1); mbar_init(bar0 + 64 + 8 * s, 2); }
    asm volatile("fence.mbarrier_init.release.cluster;" ::: "memory");
  }
  __syncthreads();
  if (tid >= 256) {
    if (tid == 256) {
      for (int it = 0; it < 20; it++) {
        const int s = it % K1_STAGES;
        mbar_wait(bar0 + 64 + 8 * s, ((it / K1_STAGES) & 1) ^ 1);
        mbar_expect_tx(bar0 + 8 * s, 16384);
        for (int b = 0; b < 4; b++)
          tma_load_2d(smem_u32(sB + s * 16384 + b * 4096), &tmW, nblk * 240 + b * 64, it * 32, bar0 + 8 * s);
      }
    }
    return;
  }
  ln_prologue(x, mblk * 128, sA, tid);
  fence_async_smem();
  named_bar_sync(1, 256);
  const int wg = tid >> 7;
  float acc[120];
#pragma unroll
  for (int i = 0; i < 120; i++) acc[i] = 0.f;
  const uint32_t aBase = smem_u32(sA) + wg * 64 * 128;
  const uint32_t bBase = smem_u32(sB);
  for (int it = 0; it < 20; it++) {
    const int s = it % K1_STAGES;
    mbar_wait(bar0 + 8 * s, (it / K1_STAGES) & 1);
    wg_fence();
#pragma unroll
    for (int kk = 0; kk < 2; kk++) {
      uint64_t da = make_desc(aBase + (it >> 1) * 16384 + (it & 1) * 64 + kk * 32, 16, 1024, 1);
      uint64_t db = make_desc(bBase + s * 16384 + kk * 2048, 4096, 1024, 1);
      wgmma_ss_n240<1>(acc, da, db, 1);
    }
    wg_commit();
    wg_wait<0>();
    if ((tid & 127) == 0) mbar_arrive(bar0 + 64 + 8 * s);
  }
  reg_fence(acc);
  const int lane = tid & 31, q = lane & 3;
  const int row = mblk * 128 + wg * 64 + ((tid & 127) >> 5) * 16 + (lane >> 2);
#pragma unroll
  for (int i = 0; i < 30; i++) {
    const int col = 8 * i + 2 * q;
    const int sl = col / 20, d = col - sl * 20;
    const size_t base = ((size_t)(nblk * 12 + sl) * SEQ + row) * 32 + d;
    *reinterpret_cast<uint32_t*>(g_qkv + base) = pack_bf16(acc[4 * i], acc[4 * i + 1]);
    *reinterpret_cast<uint32_t*>(g_qkv + base + 8 * 32) = pack_bf16(acc[4 * i + 2], acc[4 * i + 3]);
  }
  for (int t = tid; t < 128 * 12 * 3; t += 256) {
    const int part = t % 3, sl = (t / 3) % 12, r = t / 36;
    const int gs = nblk * 12 + sl;
    uint2 val = make_uint2(0u, 0u);
    if (gs >= 64 && part == 0) val.x = 0x00003F80u;
    *reinterpret_cast<uint2*>(g_qkv + ((size_t)gs * SEQ + mblk * 128 + r) * 32 + 20 + part * 4) = val;
  }
}

constexpr int K2_STAGES = 4;
constexpr int K2_SMEM = 16384 + K2_STAGES * 16384 + 1024;
__global__ void __launch_bounds__(544, 1) k2_attn(const __grid_constant__ CUtensorMap tmQKV) {
  extern __shared__ __align__(1024) uint8_t smem[];
  uint8_t* sQ = smem;
  uint8_t* sKV = smem + 16384;
  const uint32_t bar0 = smem_u32(smem + 16384 + K2_STAGES * 16384);
  const int tid = threadIdx.x;
  const int head = blockIdx.x >> 3, qblk = blockIdx.x & 7;
  if (tid == 0) {
    for (int s = 0; s < K2_STAGES; s++) { mbar_init(bar0 + 8 * s, 1); mbar_init(bar0 + 64 + 8 * s, 4); }
    mbar_init(bar0 + 128, 1);
    asm volatile("fence.mbarrier_init.release.cluster;" ::: "memory");
  }
  __syncthreads();
  if (tid >= 512) {
    if (tid == 512) {
      mbar_expect_tx(bar0 + 128, 16384);
      tma_load_2d(smem_u32(sQ), &tmQKV, 0, head * SEQ + qblk * 256, bar0 + 128);
      tma_load_2d(smem_u32(sQ) + 8192, &tmQKV, 0, head * SEQ + qblk * 256 + 128, bar0 + 128);
      for (int it = 0; it < 16; it++) {
        const int s = it % K2_STAGES;
        mbar_wait(bar0 + 64 + 8 * s, ((it / K2_STAGES) & 1) ^ 1);
        mbar_expect_tx(bar0 + 8 * s, 16384);
        tma_load_2d(smem_u32(sKV + s * 16384), &tmQKV, 0, (32 + head) * SEQ + it * 128, bar0 + 8 * s);
        tma_load_2d(smem_u32(sKV + s * 16384 + 8192), &tmQKV, 0, (64 + head) * SEQ + it * 128, bar0 + 8 * s);
      }
    }
    return;
  }
  const int wg = tid >> 7, lane = tid & 31;
  const float c = 0.22360679774997896f * 1.4426950408889634f;
  float o[12];
#pragma unroll
  for (int i = 0; i < 12; i++) o[i] = 0.f;
  float m0 = -INFINITY, m1 = -INFINITY;
  const uint32_t qBase = smem_u32(sQ) + wg * 4096;
  mbar_wait(bar0 + 128, 0);
  for (int it = 0; it < 16; it++) {
    const int s = it % K2_STAGES;
    const uint32_t kBase = smem_u32(sKV + s * 16384), vBase = kBase + 8192;
    float sc[64];
    mbar_wait(bar0 + 8 * s, (it / K2_STAGES) & 1);
    wg_fence();
#pragma unroll
    for (int kk = 0; kk < 2; kk++)
      wgmma_ss_n128<0>(sc, make_desc(qBase + kk * 32, 16, 512, 2), make_desc(kBase + kk * 32, 16, 512, 2), kk);
    wg_commit();
    wg_wait<0>();
    reg_fence(sc);
    float mx0 = m0, mx1 = m1;
#pragma unroll
    for (int i = 0; i < 16; i++) {
      mx0 = fmaxf(mx0, fmaxf(sc[4 * i], sc[4 * i + 1]));
      mx1 = fmaxf(mx1, fmaxf(sc[4 * i + 2], sc[4 * i + 3]));
    }
    mx0 = fmaxf(mx0, __shfl_xor_sync(0xffffffffu, mx0, 1)); mx0 = fmaxf(mx0, __shfl_xor_sync(0xffffffffu, mx0, 2));
    mx1 = fmaxf(mx1, __shfl_xor_sync(0xffffffffu, mx1, 1)); mx1 = fmaxf(mx1, __shfl_xor_sync(0xffffffffu, mx1, 2));
    const float a0 = exp2f((m0 - mx0) * c), a1 = exp2f((m1 - mx1) * c);
    m0 = mx0; m1 = mx1;
    const float nb0 = -mx0 * c, nb1 = -mx1 * c;
    uint32_t p[32];
#pragma unroll
    for (int i = 0; i < 16; i++) {
      p[2 * i] = pack_bf16(exp2f(fmaf(sc[4 * i], c, nb0)), exp2f(fmaf(sc[4 * i + 1], c, nb0)));
      p[2 * i + 1] = pack_bf16(exp2f(fmaf(sc[4 * i + 2], c, nb1)), exp2f(fmaf(sc[4 * i + 3], c, nb1)));
    }
#pragma unroll
    for (int i = 0; i < 3; i++) { o[4 * i] *= a0; o[4 * i + 1] *= a0; o[4 * i + 2] *= a1; o[4 * i + 3] *= a1; }
    wg_fence();
#pragma unroll
    for (int kk = 0; kk < 8; kk++)
      wgmma_rs_n24<1>(o, p[4 * kk], p[4 * kk + 1], p[4 * kk + 2], p[4 * kk + 3], make_desc(vBase + kk * 1024, 16, 512, 2), 1);
    wg_commit();
    wg_wait<0>();
    reg_fence(o);
    if ((tid & 127) == 0) mbar_arrive(bar0 + 64 + 8 * s);
  }
  const float l0 = __shfl_sync(0xffffffffu, o[8], (lane & ~3) | 2);
  const float l1 = __shfl_sync(0xffffffffu, o[10], (lane & ~3) | 2);
  const float i0 = 1.0f / l0, i1 = 1.0f / l1;
  const int q = lane & 3;
  const int row = qblk * 256 + wg * 64 + ((tid & 127) >> 5) * 16 + (lane >> 2);
#pragma unroll
  for (int i = 0; i < 3; i++) {
    const int d = 8 * i + 2 * q;
    if (d < 20) {
      *reinterpret_cast<uint32_t*>(g_o + (size_t)row * DM + head * 20 + d) = pack_bf16(o[4 * i] * i0, o[4 * i + 1] * i0);
      *reinterpret_cast<uint32_t*>(g_o + (size_t)(row + 8) * DM + head * 20 + d) = pack_bf16(o[4 * i + 2] * i1, o[4 * i + 3] * i1);
    }
  }
}

constexpr int G_STAGES = 6;
constexpr int G_STAGE_BYTES = 16384 + 16384;
constexpr int G_SMEM = G_STAGES * G_STAGE_BYTES + 1024;
template <int KTOT>
__global__ void __launch_bounds__(288, 1) k_gemm_res(const __grid_constant__ CUtensorMap tmA, const __grid_constant__ CUtensorMap tmB,
                                                     const bf16* __restrict__ res, bf16* __restrict__ out) {
  extern __shared__ __align__(1024) uint8_t smem[];
  const uint32_t bar0 = smem_u32(smem + G_STAGES * G_STAGE_BYTES);
  const int tid = threadIdx.x;
  const int mblk = blockIdx.x >> 3, nblk = blockIdx.x & 7;
  constexpr int NIT = KTOT / 64;
  if (tid == 0) {
    for (int s = 0; s < G_STAGES; s++) { mbar_init(bar0 + 8 * s, 1); mbar_init(bar0 + 64 + 8 * s, 2); }
    asm volatile("fence.mbarrier_init.release.cluster;" ::: "memory");
  }
  __syncthreads();
  if (tid >= 256) {
    if (tid == 256) {
      for (int it = 0; it < NIT; it++) {
        const int s = it % G_STAGES;
        mbar_wait(bar0 + 64 + 8 * s, ((it / G_STAGES) & 1) ^ 1);
        mbar_expect_tx(bar0 + 8 * s, G_STAGE_BYTES);
        const uint32_t st = smem_u32(smem + s * G_STAGE_BYTES);
        tma_load_2d(st, &tmA, it * 64, mblk * 128, bar0 + 8 * s);
        tma_load_2d(st + 16384, &tmB, nblk * 80, it * 64, bar0 + 8 * s);
        tma_load_2d(st + 16384 + 8192, &tmB, nblk * 80 + 64, it * 64, bar0 + 8 * s);
      }
    }
    return;
  }
  const int wg = tid >> 7;
  float acc[40];
#pragma unroll
  for (int i = 0; i < 40; i++) acc[i] = 0.f;
  for (int it = 0; it < NIT; it++) {
    const int s = it % G_STAGES;
    const uint32_t st = smem_u32(smem + s * G_STAGE_BYTES);
    mbar_wait(bar0 + 8 * s, (it / G_STAGES) & 1);
    wg_fence();
#pragma unroll
    for (int kk = 0; kk < 4; kk++) {
      uint64_t da = make_desc(st + wg * 8192 + kk * 32, 16, 1024, 1);
      uint64_t db = make_desc(st + 16384 + kk * 2048, 8192, 1024, 1);
      wgmma_ss_n80<1>(acc, da, db, 1);
    }
    wg_commit();
    wg_wait<0>();
    if ((tid & 127) == 0) mbar_arrive(bar0 + 64 + 8 * s);
  }
  reg_fence(acc);
  const int lane = tid & 31, q = lane & 3;
  const int row = mblk * 128 + wg * 64 + ((tid & 127) >> 5) * 16 + (lane >> 2);
#pragma unroll
  for (int i = 0; i < 10; i++) {
    const int col = nblk * 80 + 8 * i + 2 * q;
    const uint32_t r0 = *reinterpret_cast<const uint32_t*>(res + (size_t)row * DM + col);
    const uint32_t r1 = *reinterpret_cast<const uint32_t*>(res + (size_t)(row + 8) * DM + col);
    *reinterpret_cast<uint32_t*>(out + (size_t)row * DM + col) =
        pack_bf16(acc[4 * i] + __uint_as_float(r0 << 16), acc[4 * i + 1] + __uint_as_float(r0 & 0xffff0000u));
    *reinterpret_cast<uint32_t*>(out + (size_t)(row + 8) * DM + col) =
        pack_bf16(acc[4 * i + 2] + __uint_as_float(r1 << 16), acc[4 * i + 3] + __uint_as_float(r1 & 0xffff0000u));
  }
}

constexpr int K4_STAGES = 4;
constexpr int K4_SMEM = 163840 + K4_STAGES * 16384 + 1024;
__global__ void __launch_bounds__(288, 1) k4_ln_ffn(const __grid_constant__ CUtensorMap tmG, const __grid_constant__ CUtensorMap tmU) {
  extern __shared__ __align__(1024) uint8_t smem[];
  uint8_t* sA = smem;
  uint8_t* sB = smem + 163840;
  const uint32_t bar0 = smem_u32(smem + 163840 + K4_STAGES * 16384);
  const int tid = threadIdx.x;
  const int mblk = blockIdx.x >> 3, nblk = blockIdx.x & 7;
  if (tid == 0) {
    for (int s = 0; s < K4_STAGES; s++) { mbar_init(bar0 + 8 * s, 1); mbar_init(bar0 + 64 + 8 * s, 2); }
    asm volatile("fence.mbarrier_init.release.cluster;" ::: "memory");
  }
  __syncthreads();
  if (tid >= 256) {
    if (tid == 256) {
      for (int it = 0; it < 30; it++) {
        const int s = it % K4_STAGES;
        const int pass = it / 10, kb = it % 10;
        mbar_wait(bar0 + 64 + 8 * s, ((it / K4_STAGES) & 1) ^ 1);
        mbar_expect_tx(bar0 + 8 * s, 16384);
        tma_load_2d(smem_u32(sB + s * 16384), &tmG, nblk * 192 + pass * 64, kb * 64, bar0 + 8 * s);
        tma_load_2d(smem_u32(sB + s * 16384 + 8192), &tmU, nblk * 192 + pass * 64, kb * 64, bar0 + 8 * s);
      }
    }
    return;
  }
  ln_prologue(g_h, mblk * 128, sA, tid);
  fence_async_smem();
  named_bar_sync(1, 256);
  const int wg = tid >> 7;
  const uint32_t aBase = smem_u32(sA) + wg * 64 * 128;
  const uint32_t bBase = smem_u32(sB);
  const int lane = tid & 31, q = lane & 3;
  const int row = mblk * 128 + wg * 64 + ((tid & 127) >> 5) * 16 + (lane >> 2);
  for (int pass = 0; pass < 3; pass++) {
    float acc[64];
#pragma unroll
    for (int i = 0; i < 64; i++) acc[i] = 0.f;
    for (int kb = 0; kb < 10; kb++) {
      const int it = pass * 10 + kb;
      const int s = it % K4_STAGES;
      mbar_wait(bar0 + 8 * s, (it / K4_STAGES) & 1);
      wg_fence();
#pragma unroll
      for (int kk = 0; kk < 4; kk++) {
        uint64_t da = make_desc(aBase + kb * 16384 + kk * 32, 16, 1024, 1);
        uint64_t db = make_desc(bBase + s * 16384 + kk * 2048, 8192, 1024, 1);
        wgmma_ss_n128<1>(acc, da, db, 1);
      }
      wg_commit();
      wg_wait<0>();
      if ((tid & 127) == 0) mbar_arrive(bar0 + 64 + 8 * s);
    }
    reg_fence(acc);
#pragma unroll
    for (int i = 0; i < 8; i++) {
      const int col = nblk * 192 + pass * 64 + 8 * i + 2 * q;
      float r[4];
#pragma unroll
      for (int j = 0; j < 4; j++) {
        const float g = acc[4 * i + j], u = acc[32 + 4 * i + j];
        r[j] = g / (1.0f + __expf(-g)) * u;
      }
      *reinterpret_cast<uint32_t*>(g_act + (size_t)row * FF + col) = pack_bf16(r[0], r[1]);
      *reinterpret_cast<uint32_t*>(g_act + (size_t)(row + 8) * FF + col) = pack_bf16(r[2], r[3]);
    }
  }
}

typedef CUresult (*EncodeFn)(CUtensorMap*, CUtensorMapDataType, cuuint32_t, void*, const cuuint64_t*, const cuuint64_t*,
                             const cuuint32_t*, const cuuint32_t*, CUtensorMapInterleave, CUtensorMapSwizzle,
                             CUtensorMapL2promotion, CUtensorMapFloatOOBfill);
static void make_map(EncodeFn fn, CUtensorMap* m, const void* ptr, uint64_t cols, uint64_t rows, uint32_t bc, uint32_t br,
                     CUtensorMapSwizzle sw) {
  cuuint64_t dims[2] = {cols, rows};
  cuuint64_t strides[1] = {cols * 2};
  cuuint32_t box[2] = {bc, br};
  cuuint32_t es[2] = {1, 1};
  fn(m, CU_TENSOR_MAP_DATA_TYPE_BFLOAT16, 2, const_cast<void*>(ptr), dims, strides, box, es, CU_TENSOR_MAP_INTERLEAVE_NONE, sw,
     CU_TENSOR_MAP_L2_PROMOTION_L2_128B, CU_TENSOR_MAP_FLOAT_OOB_FILL_NONE);
}

extern "C" void kernel_launch(void* const* d_in, const int* in_sizes, int n_in, void* d_out, int out_size) {
  const bf16* x = (const bf16*)d_in[0];
  const bf16* wqkv = (const bf16*)d_in[1];
  const bf16* wo = (const bf16*)d_in[2];
  const bf16* wg = (const bf16*)d_in[4];
  const bf16* wu = (const bf16*)d_in[5];
  const bf16* wd = (const bf16*)d_in[6];
  bf16* out = (bf16*)d_out;
  static EncodeFn fn = nullptr;
  static void *p_qkv, *p_o, *p_h, *p_act;
  if (!fn) {
    void* f = nullptr;
    cudaDriverEntryPointQueryResult qr;
    cudaGetDriverEntryPoint("cuTensorMapEncodeTiled", &f, cudaEnableDefault, &qr);
    fn = (EncodeFn)f;
    cudaGetSymbolAddress(&p_qkv, g_qkv);
    cudaGetSymbolAddress(&p_o, g_o);
    cudaGetSymbolAddress(&p_h, g_h);
    cudaGetSymbolAddress(&p_act, g_act);
    cudaFuncSetAttribute(k1_ln_qkv, cudaFuncAttributeMaxDynamicSharedMemorySize, K1_SMEM);
    cudaFuncSetAttribute(k2_attn, cudaFuncAttributeMaxDynamicSharedMemorySize, K2_SMEM);
    cudaFuncSetAttribute(k_gemm_res<640>, cudaFuncAttributeMaxDynamicSharedMemorySize, G_SMEM);
    cudaFuncSetAttribute(k_gemm_res<1536>, cudaFuncAttributeMaxDynamicSharedMemorySize, G_SMEM);
    cudaFuncSetAttribute(k4_ln_ffn, cudaFuncAttributeMaxDynamicSharedMemorySize, K4_SMEM);
  }
  CUtensorMap mWqkv, mQKV, mO, mWo, mWg, mWu, mAct, mWd;
  make_map(fn, &mWqkv, wqkv, 3 * DM, DM, 64, 32, CU_TENSOR_MAP_SWIZZLE_128B);
  make_map(fn, &mQKV, p_qkv, 32, 3 * NH * SEQ, 32, 128, CU_TENSOR_MAP_SWIZZLE_64B);
  make_map(fn, &mO, p_o, DM, SEQ, 64, 128, CU_TENSOR_MAP_SWIZZLE_128B);
  make_map(fn, &mWo, wo, DM, DM, 64, 64, CU_TENSOR_MAP_SWIZZLE_128B);
  make_map(fn, &mWg, wg, FF, DM, 64, 64, CU_TENSOR_MAP_SWIZZLE_128B);
  make_map(fn, &mWu, wu, FF, DM, 64, 64, CU_TENSOR_MAP_SWIZZLE_128B);
  make_map(fn, &mAct, p_act, FF, SEQ, 64, 128, CU_TENSOR_MAP_SWIZZLE_128B);
  make_map(fn, &mWd, wd, DM, FF, 64, 64, CU_TENSOR_MAP_SWIZZLE_128B);
  k1_ln_qkv<<<128, 288, K1_SMEM>>>(x, mWqkv);
  k2_attn<<<256, 544, K2_SMEM>>>(mQKV);
  k_gemm_res<640><<<128, 288, G_SMEM>>>(mO, mWo, x, (bf16*)p_h);
  k4_ln_ffn<<<128, 288, K4_SMEM>>>(mWg, mWu);
  k_gemm_res<1536><<<128, 288, G_SMEM>>>(mAct, mWd, (const bf16*)p_h, out);
}
```

```cpp
#include <cuda_runtime.h>
#include <cuda_bf16.h>
#include <cuda.h>
#include <stdint.h>

typedef __nv_bfloat16 bf16;

constexpr int SEQ = 2048, DM = 640, NH = 32, DH = 20, FF = 1536;

__device__ __align__(1024) bf16 g_qkv[3 * NH * SEQ * 32];
__device__ __align__(1024) bf16 g_o[SEQ * DM];
__device__ __align__(1024) bf16 g_h[SEQ * DM];
__device__ __align__(1024) bf16 g_act[SEQ * FF];

__device__ __forceinline__ uint32_t smem_u32(const void* p) { return (uint32_t)__cvta_generic_to_shared(p); }
__device__ __forceinline__ void mbar_init(uint32_t bar, uint32_t count) {
  asm volatile("mbarrier.init.shared::cta.b64 [%0], %1;" :: "r"(bar), "r"(count) : "memory");
}
__device__ __forceinline__ void mbar_expect_tx(uint32_t bar, uint32_t bytes) {
  asm volatile("mbarrier.arrive.expect_tx.shared::cta.b64 _, [%0], %1;" :: "r"(bar), "r"(bytes) : "memory");
}
__device__ __forceinline__ void mbar_arrive(uint32_t bar) {
  asm volatile("mbarrier.arrive.shared::cta.b64 _, [%0];" :: "r"(bar) : "memory");
}
__device__ __forceinline__ void mbar_wait(uint32_t bar, uint32_t parity) {
  uint32_t done;
  uint32_t it = 0;
  do {
    asm volatile("{\n.reg .pred p;\nmbarrier.try_wait.parity.shared::cta.b64 p, [%1], %2;\nselp.u32 %0, 1, 0, p;\n}"
                 : "=r"(done) : "r"(bar), "r"(parity) : "memory");
    if (++it > 4000000u) __trap();
  } while (!done);
}
__device__ __forceinline__ void tma_load_2d(uint32_t dst, const CUtensorMap* map, int c0, int c1, uint32_t bar) {
  asm volatile("cp.async.bulk.tensor.2d.shared::cluster.global.mbarrier::complete_tx::bytes [%0], [%1, {%3, %4}], [%2];"
               :: "r"(dst), "l"((uint64_t)map), "r"(bar), "r"(c0), "r"(c1) : "memory");
}
__device__ __forceinline__ void fence_async_smem() { asm volatile("fence.proxy.async.shared::cta;" ::: "memory"); }
__device__ __forceinline__ void wg_fence() { asm volatile("wgmma.fence.sync.aligned;" ::: "memory"); }
__device__ __forceinline__ void wg_commit() { asm volatile("wgmma.commit_group.sync.aligned;" ::: "memory"); }
template <int N> __device__ __forceinline__ void wg_wait() { asm volatile("wgmma.wait_group.sync.aligned %0;" :: "n"(N) : "memory"); }
template <int N> __device__ __forceinline__ void reg_fence(float (&d)[N]) {
#pragma unroll
  for (int i = 0; i < N; i++) asm volatile("" : "+f"(d[i]) :: "memory");
}
__device__ __forceinline__ uint64_t make_desc(uint32_t addr, uint32_t lbo, uint32_t sbo, uint32_t swz) {
  return (uint64_t)((addr & 0x3FFFF) >> 4) | ((uint64_t)(lbo >> 4) << 16) | ((uint64_t)(sbo >> 4) << 32) | ((uint64_t)swz << 62);
}
__device__ __forceinline__ uint32_t pack_bf16(float a, float b) {
  __nv_bfloat162 v = __floats2bfloat162_rn(a, b);
  return *reinterpret_cast<uint32_t*>(&v);
}
__device__ __forceinline__ float ex2(float x) { float y; asm("ex2.approx.ftz.f32 %0, %1;" : "=f"(y) : "f"(x)); return y; }
__device__ __forceinline__ void named_bar_sync(int id, int n) { asm volatile("bar.sync %0, %1;" :: "r"(id), "r"(n) : "memory"); }

template<int TB> __device__ __forceinline__ void wgmma_ss_n240(float (&d)[120], uint64_t descA, uint64_t descB, int scaleD) {
  asm volatile("{\n.reg .pred p;\nsetp.ne.b32 p, %122, 0;\n"
    "wgmma.mma_async.sync.aligned.m64n240k16.f32.bf16.bf16 {%0, %1, %2, %3, %4, %5, %6, %7, %8, %9, %10, %11, %12, %13, %14, %15, %16, %17, %18, %19, %20, %21, %22, %23, %24, %25, %26, %27, %28, %29, %30, %31, %32, %33, %34, %35, %36, %37, %38, %39, %40, %41, %42, %43, %44, %45, %46, %47, %48, %49, %50, %51, %52, %53, %54, %55, %56, %57, %58, %59, %60, %61, %62, %63, %64, %65, %66, %67, %68, %69, %70, %71, %72, %73, %74, %75, %76, %77, %78, %79, %80, %81, %82, %83, %84, %85, %86, %87, %88, %89, %90, %91, %92, %93, %94, %95, %96, %97, %98, %99, %100, %101, %102, %103, %104, %105, %106, %107, %108, %109, %110, %111, %112, %113, %114, %115, %116, %117, %118, %119}, %120, %121, p, 1, 1, 0, %123;\n}"
    : "+f"(d[0]), "+f"(d[1]), "+f"(d[2]), "+f"(d[3]), "+f"(d[4]), "+f"(d[5]), "+f"(d[6]), "+f"(d[7]), "+f"(d[8]), "+f"(d[9]), "+f"(d[10]), "+f"(d[11]), "+f"(d[12]), "+f"(d[13]), "+f"(d[14]), "+f"(d[15]), "+f"(d[16]), "+f"(d[17]), "+f"(d[18]), "+f"(d[19]), "+f"(d[20]), "+f"(d[21]), "+f"(d[22]), "+f"(d[23]), "+f"(d[24]), "+f"(d[25]), "+f"(d[26]), "+f"(d[27]), "+f"(d[28]), "+f"(d[29]), "+f"(d[30]), "+f"(d[31]), "+f"(d[32]), "+f"(d[33]), "+f"(d[34]), "+f"(d[35]), "+f"(d[36]), "+f"(d[37]), "+f"(d[38]), "+f"(d[39]), "+f"(d[40]), "+f"(d[41]), "+f"(d[42]), "+f"(d[43]), "+f"(d[44]), "+f"(d[45]), "+f"(d[46]), "+f"(d[47]), "+f"(d[48]), "+f"(d[49]), "+f"(d[50]), "+f"(d[51]), "+f"(d[52]), "+f"(d[53]), "+f"(d[54]), "+f"(d[55]), "+f"(d[56]), "+f"(d[57]), "+f"(d[58]), "+f"(d[59]), "+f"(d[60]), "+f"(d[61]), "+f"(d[62]), "+f"(d[63]), "+f"(d[64]), "+f"(d[65]), "+f"(d[66]), "+f"(d[67]), "+f"(d[68]), "+f"(d[69]), "+f"(d[70]), "+f"(d[71]), "+f"(d[72]), "+f"(d[73]), "+f"(d[74]), "+f"(d[75]), "+f"(d[76]), "+f"(d[77]), "+f"(d[78]), "+f"(d[79]), "+f"(d[80]), "+f"(d[81]), "+f"(d[82]), "+f"(d[83]), "+f"(d[84]), "+f"(d[85]), "+f"(d[86]), "+f"(d[87]), "+f"(d[88]), "+f"(d[89]), "+f"(d[90]), "+f"(d[91]), "+f"(d[92]), "+f"(d[93]), "+f"(d[94]), "+f"(d[95]), "+f"(d[96]), "+f"(d[97]), "+f"(d[98]), "+f"(d[99]), "+f"(d[100]), "+f"(d[101]), "+f"(d[102]), "+f"(d[103]), "+f"(d[104]), "+f"(d[105]), "+f"(d[106]), "+f"(d[107]), "+f"(d[108]), "+f"(d[109]), "+f"(d[110]), "+f"(d[111]), "+f"(d[112]), "+f"(d[113]), "+f"(d[114]), "+f"(d[115]), "+f"(d[116]), "+f"(d[117]), "+f"(d[118]), "+f"(d[119])
    : "l"(descA), "l"(descB), "r"(scaleD), "n"(TB));
}
template<int TB> __device__ __forceinline__ void wgmma_ss_n128(float (&d)[64], uint64_t descA, uint64_t descB, int scaleD) {
  asm volatile("{\n.reg .pred p;\nsetp.ne.b32 p, %66, 0;\n"
    "wgmma.mma_async.sync.aligned.m64n128k16.f32.bf16.bf16 {%0, %1, %2, %3, %4, %5, %6, %7, %8, %9, %10, %11, %12, %13, %14, %15, %16, %17, %18, %19, %20, %21, %22, %23, %24, %25, %26, %27, %28, %29, %30, %31, %32, %33, %34, %35, %36, %37, %38, %39, %40, %41, %42, %43, %44, %45, %46, %47, %48, %49, %50, %51, %52, %53, %54, %55, %56, %57, %58, %59, %60, %61, %62, %63}, %64, %65, p, 1, 1, 0, %67;\n}"
    : "+f"(d[0]), "+f"(d[1]), "+f"(d[2]), "+f"(d[3]), "+f"(d[4]), "+f"(d[5]), "+f"(d[6]), "+f"(d[7]), "+f"(d[8]), "+f"(d[9]), "+f"(d[10]), "+f"(d[11]), "+f"(d[12]), "+f"(d[13]), "+f"(d[14]), "+f"(d[15]), "+f"(d[16]), "+f"(d[17]), "+f"(d[18]), "+f"(d[19]), "+f"(d[20]), "+f"(d[21]), "+f"(d[22]), "+f"(d[23]), "+f"(d[24]), "+f"(d[25]), "+f"(d[26]), "+f"(d[27]), "+f"(d[28]), "+f"(d[29]), "+f"(d[30]), "+f"(d[31]), "+f"(d[32]), "+f"(d[33]), "+f"(d[34]), "+f"(d[35]), "+f"(d[36]), "+f"(d[37]), "+f"(d[38]), "+f"(d[39]), "+f"(d[40]), "+f"(d[41]), "+f"(d[42]), "+f"(d[43]), "+f"(d[44]), "+f"(d[45]), "+f"(d[46]), "+f"(d[47]), "+f"(d[48]), "+f"(d[49]), "+f"(d[50]), "+f"(d[51]), "+f"(d[52]), "+f"(d[53]), "+f"(d[54]), "+f"(d[55]), "+f"(d[56]), "+f"(d[57]), "+f"(d[58]), "+f"(d[59]), "+f"(d[60]), "+f"(d[61]), "+f"(d[62]), "+f"(d[63])
    : "l"(descA), "l"(descB), "r"(scaleD), "n"(TB));
}
template<int TB> __device__ __forceinline__ void wgmma_ss_n80(float (&d)[40], uint64_t descA, uint64_t descB, int scaleD) {
  asm volatile("{\n.reg .pred p;\nsetp.ne.b32 p, %42, 0;\n"
    "wgmma.mma_async.sync.aligned.m64n80k16.f32.bf16.bf16 {%0, %1, %2, %3, %4, %5, %6, %7, %8, %9, %10, %11, %12, %13, %14, %15, %16, %17, %18, %19, %20, %21, %22, %23, %24, %25, %26, %27, %28, %29, %30, %31, %32, %33, %34, %35, %36, %37, %38, %39}, %40, %41, p, 1, 1, 0, %43;\n}"
    : "+f"(d[0]), "+f"(d[1]), "+f"(d[2]), "+f"(d[3]), "+f"(d[4]), "+f"(d[5]), "+f"(d[6]), "+f"(d[7]), "+f"(d[8]), "+f"(d[9]), "+f"(d[10]), "+f"(d[11]), "+f"(d[12]), "+f"(d[13]), "+f"(d[14]), "+f"(d[15]), "+f"(d[16]), "+f"(d[17]), "+f"(d[18]), "+f"(d[19]), "+f"(d[20]), "+f"(d[21]), "+f"(d[22]), "+f"(d[23]), "+f"(d[24]), "+f"(d[25]), "+f"(d[26]), "+f"(d[27]), "+f"(d[28]), "+f"(d[29]), "+f"(d[30]), "+f"(d[31]), "+f"(d[32]), "+f"(d[33]), "+f"(d[34]), "+f"(d[35]), "+f"(d[36]), "+f"(d[37]), "+f"(d[38]), "+f"(d[39])
    : "l"(descA), "l"(descB), "r"(scaleD), "n"(TB));
}
template<int TB> __device__ __forceinline__ void wgmma_rs_n24(float (&d)[12], uint32_t a0, uint32_t a1, uint32_t a2, uint32_t a3, uint64_t descB, int scaleD) {
  asm volatile("{\n.reg .pred p;\nsetp.ne.b32 p, %17, 0;\n"
    "wgmma.mma_async.sync.aligned.m64n24k16.f32.bf16.bf16 {%0, %1, %2, %3, %4, %5, %6, %7, %8, %9, %10, %11}, {%12, %13, %14, %15}, %16, p, 1, 1, %18;\n}"
    : "+f"(d[0]), "+f"(d[1]), "+f"(d[2]), "+f"(d[3]), "+f"(d[4]), "+f"(d[5]), "+f"(d[6]), "+f"(d[7]), "+f"(d[8]), "+f"(d[9]), "+f"(d[10]), "+f"(d[11])
    : "r"(a0), "r"(a1), "r"(a2), "r"(a3), "l"(descB), "r"(scaleD), "n"(TB));
}


__device__ __forceinline__ void ln_prologue(const bf16* __restrict__ src, int row0, uint8_t* sA, int ctid) {
  const int warp = ctid >> 5, lane = ctid & 31;
  for (int rr = 0; rr < 16; rr += 8) {
    uint2 v[8][5];
#pragma unroll
    for (int u = 0; u < 8; u++) {
      const uint2* p = reinterpret_cast<const uint2*>(src + (size_t)(row0 + warp * 16 + rr + u) * DM);
#pragma unroll
      for (int j = 0; j < 5; j++) v[u][j] = p[lane + 32 * j];
    }
#pragma unroll
    for (int u = 0; u < 8; u++) {
      float f[20];
#pragma unroll
      for (int j = 0; j < 5; j++) {
        f[4 * j + 0] = __uint_as_float(v[u][j].x << 16);
        f[4 * j + 1] = __uint_as_float(v[u][j].x & 0xffff0000u);
        f[4 * j + 2] = __uint_as_float(v[u][j].y << 16);
        f[4 * j + 3] = __uint_as_float(v[u][j].y & 0xffff0000u);
      }
      float s = 0.f;
#pragma unroll
      for (int j = 0; j < 20; j++) s += f[j];
#pragma unroll
      for (int o = 16; o > 0; o >>= 1) s += __shfl_xor_sync(0xffffffffu, s, o);
      const float mean = s * (1.0f / DM);
      float q = 0.f;
#pragma unroll
      for (int j = 0; j < 20; j++) { f[j] -= mean; q += f[j] * f[j]; }
#pragma unroll
      for (int o = 16; o > 0; o >>= 1) q += __shfl_xor_sync(0xffffffffu, q, o);
      const float rstd = rsqrtf(q * (1.0f / DM) + 1e-5f);
      const int r = warp * 16 + rr + u;
#pragma unroll
      for (int j = 0; j < 5; j++) {
        const int e = (lane + 32 * j) * 4;
        const int kb = e >> 6;
        const int byte = (e & 63) * 2;
        const int chunk = byte >> 4;
        const int sw = ((chunk ^ (r & 7)) << 4) | (byte & 15);
        uint2 o;
        o.x = pack_bf16(f[4 * j + 0] * rstd, f[4 * j + 1] * rstd);
        o.y = pack_bf16(f[4 * j + 2] * rstd, f[4 * j + 3] * rstd);
        *reinterpret_cast<uint2*>(sA + kb * 16384 + r * 128 + sw) = o;
      }
    }
  }
}

constexpr int K1_STAGES = 4;
constexpr int K1_SMEM = 163840 + K1_STAGES * 16384 + 1024;
__global__ void __launch_bounds__(288, 1) k1_ln_qkv(const bf16* __restrict__ x, const __grid_constant__ CUtensorMap tmW) {
  extern __shared__ __align__(1024) uint8_t smem[];
  uint8_t* sA = smem;
  uint8_t* sB = smem + 163840;
  const uint32_t bar0 = smem_u32(smem + 163840 + K1_STAGES * 16384);
  const int tid = threadIdx.x;
  const int mblk = blockIdx.x >> 3, nblk = blockIdx.x & 7;
  if (tid == 0) {
    for (int s = 0; s < K1_STAGES; s++) { mbar_init(bar0 + 8 * s, 1); mbar_init(bar0 + 64 + 8 * s, 2); }
    asm volatile("fence.mbarrier_init.release.cluster;" ::: "memory");
  }
  __syncthreads();
  if (tid >= 256) {
    if (tid == 256) {
      for (int it = 0; it < 20; it++) {
        const int s = it % K1_STAGES;
        mbar_wait(bar0 + 64 + 8 * s, ((it / K1_STAGES) & 1) ^ 1);
        mbar_expect_tx(bar0 + 8 * s, 16384);
        for (int b = 0; b < 4; b++)
          tma_load_2d(smem_u32(sB + s * 16384 + b * 4096), &tmW, nblk * 240 + b * 64, it * 32, bar0 + 8 * s);
      }
    }
    return;
  }
  ln_prologue(x, mblk * 128, sA, tid);
  fence_async_smem();
  named_bar_sync(1, 256);
  const int wg = tid >> 7;
  float acc[120];
#pragma unroll
  for (int i = 0; i < 120; i++) acc[i] = 0.f;
  const uint32_t aBase = smem_u32(sA) + wg * 64 * 128;
  const uint32_t bBase = smem_u32(sB);
  for (int it = 0; it < 20; it++) {
    const int s = it % K1_STAGES;
    mbar_wait(bar0 + 8 * s, (it / K1_STAGES) & 1);
    wg_fence();
#pragma unroll
    for (int kk = 0; kk < 2; kk++) {
      uint64_t da = make_desc(aBase + (it >> 1) * 16384 + (it & 1) * 64 + kk * 32, 16, 1024, 1);
      uint64_t db = make_desc(bBase + s * 16384 + kk * 2048, 4096, 1024, 1);
      wgmma_ss_n240<1>(acc, da, db, 1);
    }
    wg_commit();
    wg_wait<1>();
    if (it > 0 && (tid & 127) == 0) mbar_arrive(bar0 + 64 + 8 * ((it - 1) % K1_STAGES));
  }
  wg_wait<0>();
  reg_fence(acc);
  const int lane = tid & 31, q = lane & 3;
  const int row = mblk * 128 + wg * 64 + ((tid & 127) >> 5) * 16 + (lane >> 2);
#pragma unroll
  for (int i = 0; i < 30; i++) {
    const int col = 8 * i + 2 * q;
    const int sl = col / 20, d = col - sl * 20;
    const size_t base = ((size_t)(nblk * 12 + sl) * SEQ + row) * 32 + d;
    *reinterpret_cast<uint32_t*>(g_qkv + base) = pack_bf16(acc[4 * i], acc[4 * i + 1]);
    *reinterpret_cast<uint32_t*>(g_qkv + base + 8 * 32) = pack_bf16(acc[4 * i + 2], acc[4 * i + 3]);
  }
  for (int t = tid; t < 128 * 12 * 3; t += 256) {
    const int part = t % 3, sl = (t / 3) % 12, r = t / 36;
    const int gs = nblk * 12 + sl;
    uint2 val = make_uint2(0u, 0u);
    if (gs >= 64 && part == 0) val.x = 0x00003F80u;
    *reinterpret_cast<uint2*>(g_qkv + ((size_t)gs * SEQ + mblk * 128 + r) * 32 + 20 + part * 4) = val;
  }
}

constexpr int K2_STAGES = 4;
constexpr int K2_SMEM = 16384 + K2_STAGES * 16384 + 1024;
__global__ void __launch_bounds__(544, 1) k2_attn(const __grid_constant__ CUtensorMap tmQKV) {
  extern __shared__ __align__(1024) uint8_t smem[];
  uint8_t* sQ = smem;
  uint8_t* sKV = smem + 16384;
  const uint32_t bar0 = smem_u32(smem + 16384 + K2_STAGES * 16384);
  const int tid = threadIdx.x;
  const int head = blockIdx.x >> 3, qblk = blockIdx.x & 7;
  if (tid == 0) {
    for (int s = 0; s < K2_STAGES; s++) { mbar_init(bar0 + 8 * s, 1); mbar_init(bar0 + 64 + 8 * s, 4); }
    mbar_init(bar0 + 128, 1);
    asm volatile("fence.mbarrier_init.release.cluster;" ::: "memory");
  }
  __syncthreads();
  if (tid >= 512) {
    if (tid == 512) {
      mbar_expect_tx(bar0 + 128, 16384);
      tma_load_2d(smem_u32(sQ), &tmQKV, 0, head * SEQ + qblk * 256, bar0 + 128);
      tma_load_2d(smem_u32(sQ) + 8192, &tmQKV, 0, head * SEQ + qblk * 256 + 128, bar0 + 128);
      for (int it = 0; it < 16; it++) {
        const int s = it % K2_STAGES;
        mbar_wait(bar0 + 64 + 8 * s, ((it / K2_STAGES) & 1) ^ 1);
        mbar_expect_tx(bar0 + 8 * s, 16384);
        tma_load_2d(smem_u32(sKV + s * 16384), &tmQKV, 0, (32 + head) * SEQ + it * 128, bar0 + 8 * s);
        tma_load_2d(smem_u32(sKV + s * 16384 + 8192), &tmQKV, 0, (64 + head) * SEQ + it * 128, bar0 + 8 * s);
      }
    }
    return;
  }
  const int wg = tid >> 7, lane = tid & 31;
  const float c = 0.22360679774997896f * 1.4426950408889634f;
  float o[12];
#pragma unroll
  for (int i = 0; i < 12; i++) o[i] = 0.f;
  float m0 = -INFINITY, m1 = -INFINITY;
  const uint32_t qBase = smem_u32(sQ) + wg * 4096;
  mbar_wait(bar0 + 128, 0);
  for (int it = 0; it < 16; it++) {
    const int s = it % K2_STAGES;
    const uint32_t kBase = smem_u32(sKV + s * 16384), vBase = kBase + 8192;
    float sc[64];
    mbar_wait(bar0 + 8 * s, (it / K2_STAGES) & 1);
    wg_fence();
#pragma unroll
    for (int kk = 0; kk < 2; kk++)
      wgmma_ss_n128<0>(sc, make_desc(qBase + kk * 32, 16, 512, 2), make_desc(kBase + kk * 32, 16, 512, 2), kk);
    wg_commit();
    wg_wait<0>();
    reg_fence(sc);
    float mx0 = m0, mx1 = m1;
#pragma unroll
    for (int i = 0; i < 16; i++) {
      mx0 = fmaxf(mx0, fmaxf(sc[4 * i], sc[4 * i + 1]));
      mx1 = fmaxf(mx1, fmaxf(sc[4 * i + 2], sc[4 * i + 3]));
    }
    mx0 = fmaxf(mx0, __shfl_xor_sync(0xffffffffu, mx0, 1)); mx0 = fmaxf(mx0, __shfl_xor_sync(0xffffffffu, mx0, 2));
    mx1 = fmaxf(mx1, __shfl_xor_sync(0xffffffffu, mx1, 1)); mx1 = fmaxf(mx1, __shfl_xor_sync(0xffffffffu, mx1, 2));
    const float a0 = ex2((m0 - mx0) * c), a1 = ex2((m1 - mx1) * c);
    m0 = mx0; m1 = mx1;
    const float nb0 = -mx0 * c, nb1 = -mx1 * c;
    uint32_t p[32];
#pragma unroll
    for (int i = 0; i < 16; i++) {
      p[2 * i] = pack_bf16(ex2(fmaf(sc[4 * i], c, nb0)), ex2(fmaf(sc[4 * i + 1], c, nb0)));
      p[2 * i + 1] = pack_bf16(ex2(fmaf(sc[4 * i + 2], c, nb1)), ex2(fmaf(sc[4 * i + 3], c, nb1)));
    }
#pragma unroll
    for (int i = 0; i < 3; i++) { o[4 * i] *= a0; o[4 * i + 1] *= a0; o[4 * i + 2] *= a1; o[4 * i + 3] *= a1; }
    wg_fence();
#pragma unroll
    for (int kk = 0; kk < 8; kk++)
      wgmma_rs_n24<1>(o, p[4 * kk], p[4 * kk + 1], p[4 * kk + 2], p[4 * kk + 3], make_desc(vBase + kk * 1024, 16, 512, 2), 1);
    wg_commit();
    wg_wait<0>();
    reg_fence(o);
    if ((tid & 127) == 0) mbar_arrive(bar0 + 64 + 8 * s);
  }
  const float l0 = __shfl_sync(0xffffffffu, o[8], (lane & ~3) | 2);
  const float l1 = __shfl_sync(0xffffffffu, o[10], (lane & ~3) | 2);
  const float i0 = 1.0f / l0, i1 = 1.0f / l1;
  const int q = lane & 3;
  const int row = qblk * 256 + wg * 64 + ((tid & 127) >> 5) * 16 + (lane >> 2);
#pragma unroll
  for (int i = 0; i < 3; i++) {
    const int d = 8 * i + 2 * q;
    if (d < 20) {
      *reinterpret_cast<uint32_t*>(g_o + (size_t)row * DM + head * 20 + d) = pack_bf16(o[4 * i] * i0, o[4 * i + 1] * i0);
      *reinterpret_cast<uint32_t*>(g_o + (size_t)(row + 8) * DM + head * 20 + d) = pack_bf16(o[4 * i + 2] * i1, o[4 * i + 3] * i1);
    }
  }
}

constexpr int G_STAGES = 6;
constexpr int G_STAGE_BYTES = 16384 + 16384;
constexpr int G_SMEM = G_STAGES * G_STAGE_BYTES + 1024;
template <int KTOT>
__global__ void __launch_bounds__(288, 1) k_gemm_res(const __grid_constant__ CUtensorMap tmA, const __grid_constant__ CUtensorMap tmB,
                                                     const bf16* __restrict__ res, bf16* __restrict__ out) {
  extern __shared__ __align__(1024) uint8_t smem[];
  const uint32_t bar0 = smem_u32(smem + G_STAGES * G_STAGE_BYTES);
  const int tid = threadIdx.x;
  const int mblk = blockIdx.x >> 3, nblk = blockIdx.x & 7;
  constexpr int NIT = KTOT / 64;
  if (tid == 0) {
    for (int s = 0; s < G_STAGES; s++) { mbar_init(bar0 + 8 * s, 1); mbar_init(bar0 + 64 + 8 * s, 2); }
    asm volatile("fence.mbarrier_init.release.cluster;" ::: "memory");
  }
  __syncthreads();
  if (tid >= 256) {
    if (tid == 256) {
      for (int it = 0; it < NIT; it++) {
        const int s = it % G_STAGES;
        mbar_wait(bar0 + 64 + 8 * s, ((it / G_STAGES) & 1) ^ 1);
        mbar_expect_tx(bar0 + 8 * s, G_STAGE_BYTES);
        const uint32_t st = smem_u32(smem + s * G_STAGE_BYTES);
        tma_load_2d(st, &tmA, it * 64, mblk * 128, bar0 + 8 * s);
        tma_load_2d(st + 16384, &tmB, nblk * 80, it * 64, bar0 + 8 * s);
        tma_load_2d(st + 16384 + 8192, &tmB, nblk * 80 + 64, it * 64, bar0 + 8 * s);
      }
    }
    return;
  }
  const int wg = tid >> 7;
  float acc[40];
#pragma unroll
  for (int i = 0; i < 40; i++) acc[i] = 0.f;
  for (int it = 0; it < NIT; it++) {
    const int s = it % G_STAGES;
    const uint32_t st = smem_u32(smem + s * G_STAGE_BYTES);
    mbar_wait(bar0 + 8 * s, (it / G_STAGES) & 1);
    wg_fence();
#pragma unroll
    for (int kk = 0; kk < 4; kk++) {
      uint64_t da = make_desc(st + wg * 8192 + kk * 32, 16, 1024, 1);
      uint64_t db = make_desc(st + 16384 + kk * 2048, 8192, 1024, 1);
      wgmma_ss_n80<1>(acc, da, db, 1);
    }
    wg_commit();
    wg_wait<1>();
    if (it > 0 && (tid & 127) == 0) mbar_arrive(bar0 + 64 + 8 * ((it - 1) % G_STAGES));
  }
  wg_wait<0>();
  reg_fence(acc);
  const int lane = tid & 31, q = lane & 3;
  const int row = mblk * 128 + wg * 64 + ((tid & 127) >> 5) * 16 + (lane >> 2);
#pragma unroll
  for (int i = 0; i < 10; i++) {
    const int col = nblk * 80 + 8 * i + 2 * q;
    const uint32_t r0 = *reinterpret_cast<const uint32_t*>(res + (size_t)row * DM + col);
    const uint32_t r1 = *reinterpret_cast<const uint32_t*>(res + (size_t)(row + 8) * DM + col);
    *reinterpret_cast<uint32_t*>(out + (size_t)row * DM + col) =
        pack_bf16(acc[4 * i] + __uint_as_float(r0 << 16), acc[4 * i + 1] + __uint_as_float(r0 & 0xffff0000u));
    *reinterpret_cast<uint32_t*>(out + (size_t)(row + 8) * DM + col) =
        pack_bf16(acc[4 * i + 2] + __uint_as_float(r1 << 16), acc[4 * i + 3] + __uint_as_float(r1 & 0xffff0000u));
  }
}

constexpr int K4_STAGES = 4;
constexpr int K4_SMEM = 163840 + K4_STAGES * 16384 + 1024;
__global__ void __launch_bounds__(288, 1) k4_ln_ffn(const __grid_constant__ CUtensorMap tmG, const __grid_constant__ CUtensorMap tmU) {
  extern __shared__ __align__(1024) uint8_t smem[];
  uint8_t* sA = smem;
  uint8_t* sB = smem + 163840;
  const uint32_t bar0 = smem_u32(smem + 163840 + K4_STAGES * 16384);
  const int tid = threadIdx.x;
  const int mblk = blockIdx.x >> 3, nblk = blockIdx.x & 7;
  if (tid == 0) {
    for (int s = 0; s < K4_STAGES; s++) { mbar_init(bar0 + 8 * s, 1); mbar_init(bar0 + 64 + 8 * s, 2); }
    asm volatile("fence.mbarrier_init.release.cluster;" ::: "memory");
  }
  __syncthreads();
  if (tid >= 256) {
    if (tid == 256) {
      for (int it = 0; it < 30; it++) {
        const int s = it % K4_STAGES;
        const int pass = it / 10, kb = it % 10;
        mbar_wait(bar0 + 64 + 8 * s, ((it / K4_STAGES) & 1) ^ 1);
        mbar_expect_tx(bar0 + 8 * s, 16384);
        tma_load_2d(smem_u32(sB + s * 16384), &tmG, nblk * 192 + pass * 64, kb * 64, bar0 + 8 * s);
        tma_load_2d(smem_u32(sB + s * 16384 + 8192), &tmU, nblk * 192 + pass * 64, kb * 64, bar0 + 8 * s);
      }
    }
    return;
  }
  ln_prologue(g_h, mblk * 128, sA, tid);
  fence_async_smem();
  named_bar_sync(1, 256);
  const int wg = tid >> 7;
  const uint32_t aBase = smem_u32(sA) + wg * 64 * 128;
  const uint32_t bBase = smem_u32(sB);
  const int lane = tid & 31, q = lane & 3;
  const int row = mblk * 128 + wg * 64 + ((tid & 127) >> 5) * 16 + (lane >> 2);
  for (int pass = 0; pass < 3; pass++) {
    float acc[64];
#pragma unroll
    for (int i = 0; i < 64; i++) acc[i] = 0.f;
    for (int kb = 0; kb < 10; kb++) {
      const int it = pass * 10 + kb;
      const int s = it % K4_STAGES;
      mbar_wait(bar0 + 8 * s, (it / K4_STAGES) & 1);
      wg_fence();
#pragma unroll
      for (int kk = 0; kk < 4; kk++) {
        uint64_t da = make_desc(aBase + kb * 16384 + kk * 32, 16, 1024, 1);
        uint64_t db = make_desc(bBase + s * 16384 + kk * 2048, 8192, 1024, 1);
        wgmma_ss_n128<1>(acc, da, db, 1);
      }
      wg_commit();
      wg_wait<1>();
      if (kb > 0 && (tid & 127) == 0) mbar_arrive(bar0 + 64 + 8 * ((it - 1) % K4_STAGES));
    }
    wg_wait<0>();
    if ((tid & 127) == 0) mbar_arrive(bar0 + 64 + 8 * ((pass * 10 + 9) % K4_STAGES));
    reg_fence(acc);
#pragma unroll
    for (int i = 0; i < 8; i++) {
      const int col = nblk * 192 + pass * 64 + 8 * i + 2 * q;
      float r[4];
#pragma unroll
      for (int j = 0; j < 4; j++) {
        const float g = acc[4 * i + j], u = acc[32 + 4 * i + j];
        r[j] = g / (1.0f + __expf(-g)) * u;
      }
      *reinterpret_cast<uint32_t*>(g_act + (size_t)row * FF + col) = pack_bf16(r[0], r[1]);
      *reinterpret_cast<uint32_t*>(g_act + (size_t)(row + 8) * FF + col) = pack_bf16(r[2], r[3]);
    }
  }
}

typedef CUresult (*EncodeFn)(CUtensorMap*, CUtensorMapDataType, cuuint32_t, void*, const cuuint64_t*, const cuuint64_t*,
                             const cuuint32_t*, const cuuint32_t*, CUtensorMapInterleave, CUtensorMapSwizzle,
                             CUtensorMapL2promotion, CUtensorMapFloatOOBfill);
static void make_map(EncodeFn fn, CUtensorMap* m, const void* ptr, uint64_t cols, uint64_t rows, uint32_t bc, uint32_t br,
                     CUtensorMapSwizzle sw) {
  cuuint64_t dims[2] = {cols, rows};
  cuuint64_t strides[1] = {cols * 2};
  cuuint32_t box[2] = {bc, br};
  cuuint32_t es[2] = {1, 1};
  fn(m, CU_TENSOR_MAP_DATA_TYPE_BFLOAT16, 2, const_cast<void*>(ptr), dims, strides, box, es, CU_TENSOR_MAP_INTERLEAVE_NONE, sw,
     CU_TENSOR_MAP_L2_PROMOTION_L2_128B, CU_TENSOR_MAP_FLOAT_OOB_FILL_NONE);
}

extern "C" void kernel_launch(void* const* d_in, const int* in_sizes, int n_in, void* d_out, int out_size) {
  const bf16* x = (const bf16*)d_in[0];
  const bf16* wqkv = (const bf16*)d_in[1];
  const bf16* wo = (const bf16*)d_in[2];
  const bf16* wg = (const bf16*)d_in[4];
  const bf16* wu = (const bf16*)d_in[5];
  const bf16* wd = (const bf16*)d_in[6];
  bf16* out = (bf16*)d_out;
  static EncodeFn fn = nullptr;
  static void *p_qkv, *p_o, *p_h, *p_act;
  if (!fn) {
    void* f = nullptr;
    cudaDriverEntryPointQueryResult qr;
    cudaGetDriverEntryPoint("cuTensorMapEncodeTiled", &f, cudaEnableDefault, &qr);
    fn = (EncodeFn)f;
    cudaGetSymbolAddress(&p_qkv, g_qkv);
    cudaGetSymbolAddress(&p_o, g_o);
    cudaGetSymbolAddress(&p_h, g_h);
    cudaGetSymbolAddress(&p_act, g_act);
    cudaFuncSetAttribute(k1_ln_qkv, cudaFuncAttributeMaxDynamicSharedMemorySize, K1_SMEM);
    cudaFuncSetAttribute(k2_attn, cudaFuncAttributeMaxDynamicSharedMemorySize, K2_SMEM);
    cudaFuncSetAttribute(k_gemm_res<640>, cudaFuncAttributeMaxDynamicSharedMemorySize, G_SMEM);
    cudaFuncSetAttribute(k_gemm_res<1536>, cudaFuncAttributeMaxDynamicSharedMemorySize, G_SMEM);
    cudaFuncSetAttribute(k4_ln_ffn, cudaFuncAttributeMaxDynamicSharedMemorySize, K4_SMEM);
  }
  CUtensorMap mWqkv, mQKV, mO, mWo, mWg, mWu, mAct, mWd;
  make_map(fn, &mWqkv, wqkv, 3 * DM, DM, 64, 32, CU_TENSOR_MAP_SWIZZLE_128B);
  make_map(fn, &mQKV, p_qkv, 32, 3 * NH * SEQ, 32, 128, CU_TENSOR_MAP_SWIZZLE_64B);
  make_map(fn, &mO, p_o, DM, SEQ, 64, 128, CU_TENSOR_MAP_SWIZZLE_128B);
  make_map(fn, &mWo, wo, DM, DM, 64, 64, CU_TENSOR_MAP_SWIZZLE_128B);
  make_map(fn, &mWg, wg, FF, DM, 64, 64, CU_TENSOR_MAP_SWIZZLE_128B);
  make_map(fn, &mWu, wu, FF, DM, 64, 64, CU_TENSOR_MAP_SWIZZLE_128B);
  make_map(fn, &mAct, p_act, FF, SEQ, 64, 128, CU_TENSOR_MAP_SWIZZLE_128B);
  make_map(fn, &mWd, wd, DM, FF, 64, 64, CU_TENSOR_MAP_SWIZZLE_128B);
  k1_ln_qkv<<<128, 288, K1_SMEM>>>(x, mWqkv);
  k2_attn<<<256, 544, K2_SMEM>>>(mQKV);
  k_gemm_res<640><<<128, 288, G_SMEM>>>(mO, mWo, x, (bf16*)p_h);
  k4_ln_ffn<<<128, 288, K4_SMEM>>>(mWg, mWu);
  k_gemm_res<1536><<<128, 288, G_SMEM>>>(mAct, mWd, (const bf16*)p_h, out);
}
```

```cpp
#include <cuda_runtime.h>
#include <cuda_bf16.h>
#include <cuda.h>
#include <stdint.h>

typedef __nv_bfloat16 bf16;

constexpr int SEQ = 2048, DM = 640, NH = 32, DH = 20, FF = 1536;

__device__ __align__(1024) bf16 g_qkv[3 * NH * SEQ * 32];
__device__ __align__(1024) bf16 g_o[SEQ * DM];
__device__ __align__(1024) bf16 g_h[SEQ * DM];
__device__ __align__(1024) bf16 g_act[SEQ * FF];

__device__ __forceinline__ uint32_t smem_u32(const void* p) { return (uint32_t)__cvta_generic_to_shared(p); }
__device__ __forceinline__ void mbar_init(uint32_t bar, uint32_t count) {
  asm volatile("mbarrier.init.shared::cta.b64 [%0], %1;" :: "r"(bar), "r"(count) : "memory");
}
__device__ __forceinline__ void mbar_expect_tx(uint32_t bar, uint32_t bytes) {
  asm volatile("mbarrier.arrive.expect_tx.shared::cta.b64 _, [%0], %1;" :: "r"(bar), "r"(bytes) : "memory");
}
__device__ __forceinline__ void mbar_arrive(uint32_t bar) {
  asm volatile("mbarrier.arrive.shared::cta.b64 _, [%0];" :: "r"(bar) : "memory");
}
__device__ __forceinline__ void mbar_wait(uint32_t bar, uint32_t parity) {
  uint32_t done;
  uint32_t it = 0;
  do {
    asm volatile("{\n.reg .pred p;\nmbarrier.try_wait.parity.shared::cta.b64 p, [%1], %2;\nselp.u32 %0, 1, 0, p;\n}"
                 : "=r"(done) : "r"(bar), "r"(parity) : "memory");
    if (++it > 4000000u) __trap();
  } while (!done);
}
__device__ __forceinline__ void tma_load_2d(uint32_t dst, const CUtensorMap* map, int c0, int c1, uint32_t bar) {
  asm volatile("cp.async.bulk.tensor.2d.shared::cluster.global.mbarrier::complete_tx::bytes [%0], [%1, {%3, %4}], [%2];"
               :: "r"(dst), "l"((uint64_t)map), "r"(bar), "r"(c0), "r"(c1) : "memory");
}
__device__ __forceinline__ void fence_async_smem() { asm volatile("fence.proxy.async.shared::cta;" ::: "memory"); }
__device__ __forceinline__ void wg_fence() { asm volatile("wgmma.fence.sync.aligned;" ::: "memory"); }
__device__ __forceinline__ void wg_commit() { asm volatile("wgmma.commit_group.sync.aligned;" ::: "memory"); }
template <int N> __device__ __forceinline__ void wg_wait() { asm volatile("wgmma.wait_group.sync.aligned %0;" :: "n"(N) : "memory"); }
template <int N> __device__ __forceinline__ void reg_fence(float (&d)[N]) {
#pragma unroll
  for (int i = 0; i < N; i++) asm volatile("" : "+f"(d[i]) :: "memory");
}
__device__ __forceinline__ uint64_t make_desc(uint32_t addr, uint32_t lbo, uint32_t sbo, uint32_t swz) {
  return (uint64_t)((addr & 0x3FFFF) >> 4) | ((uint64_t)(lbo >> 4) << 16) | ((uint64_t)(sbo >> 4) << 32) | ((uint64_t)swz << 62);
}
__device__ __forceinline__ uint32_t pack_bf16(float a, float b) {
  __nv_bfloat162 v = __floats2bfloat162_rn(a, b);
  return *reinterpret_cast<uint32_t*>(&v);
}
__device__ __forceinline__ float ex2(float x) { float y; asm("ex2.approx.ftz.f32 %0, %1;" : "=f"(y) : "f"(x)); return y; }
__device__ __forceinline__ void named_bar_sync(int id, int n) { asm volatile("bar.sync %0, %1;" :: "r"(id), "r"(n) : "memory"); }

template<int TB> __device__ __forceinline__ void wgmma_ss_n240(float (&d)[120], uint64_t descA, uint64_t descB, int scaleD) {
  asm volatile("{\n.reg .pred p;\nsetp.ne.b32 p, %122, 0;\n"
    "wgmma.mma_async.sync.aligned.m64n240k16.f32.bf16.bf16 {%0, %1, %2, %3, %4, %5, %6, %7, %8, %9, %10, %11, %12, %13, %14, %15, %16, %17, %18, %19, %20, %21, %22, %23, %24, %25, %26, %27, %28, %29, %30, %31, %32, %33, %34, %35, %36, %37, %38, %39, %40, %41, %42, %43, %44, %45, %46, %47, %48, %49, %50, %51, %52, %53, %54, %55, %56, %57, %58, %59, %60, %61, %62, %63, %64, %65, %66, %67, %68, %69, %70, %71, %72, %73, %74, %75, %76, %77, %78, %79, %80, %81, %82, %83, %84, %85, %86, %87, %88, %89, %90, %91, %92, %93, %94, %95, %96, %97, %98, %99, %100, %101, %102, %103, %104, %105, %106, %107, %108, %109, %110, %111, %112, %113, %114, %115, %116, %117, %118, %119}, %120, %121, p, 1, 1, 0, %123;\n}"
    : "+f"(d[0]), "+f"(d[1]), "+f"(d[2]), "+f"(d[3]), "+f"(d[4]), "+f"(d[5]), "+f"(d[6]), "+f"(d[7]), "+f"(d[8]), "+f"(d[9]), "+f"(d[10]), "+f"(d[11]), "+f"(d[12]), "+f"(d[13]), "+f"(d[14]), "+f"(d[15]), "+f"(d[16]), "+f"(d[17]), "+f"(d[18]), "+f"(d[19]), "+f"(d[20]), "+f"(d[21]), "+f"(d[22]), "+f"(d[23]), "+f"(d[24]), "+f"(d[25]), "+f"(d[26]), "+f"(d[27]), "+f"(d[28]), "+f"(d[29]), "+f"(d[30]), "+f"(d[31]), "+f"(d[32]), "+f"(d[33]), "+f"(d[34]), "+f"(d[35]), "+f"(d[36]), "+f"(d[37]), "+f"(d[38]), "+f"(d[39]), "+f"(d[40]), "+f"(d[41]), "+f"(d[42]), "+f"(d[43]), "+f"(d[44]), "+f"(d[45]), "+f"(d[46]), "+f"(d[47]), "+f"(d[48]), "+f"(d[49]), "+f"(d[50]), "+f"(d[51]), "+f"(d[52]), "+f"(d[53]), "+f"(d[54]), "+f"(d[55]), "+f"(d[56]), "+f"(d[57]), "+f"(d[58]), "+f"(d[59]), "+f"(d[60]), "+f"(d[61]), "+f"(d[62]), "+f"(d[63]), "+f"(d[64]), "+f"(d[65]), "+f"(d[66]), "+f"(d[67]), "+f"(d[68]), "+f"(d[69]), "+f"(d[70]), "+f"(d[71]), "+f"(d[72]), "+f"(d[73]), "+f"(d[74]), "+f"(d[75]), "+f"(d[76]), "+f"(d[77]), "+f"(d[78]), "+f"(d[79]), "+f"(d[80]), "+f"(d[81]), "+f"(d[82]), "+f"(d[83]), "+f"(d[84]), "+f"(d[85]), "+f"(d[86]), "+f"(d[87]), "+f"(d[88]), "+f"(d[89]), "+f"(d[90]), "+f"(d[91]), "+f"(d[92]), "+f"(d[93]), "+f"(d[94]), "+f"(d[95]), "+f"(d[96]), "+f"(d[97]), "+f"(d[98]), "+f"(d[99]), "+f"(d[100]), "+f"(d[101]), "+f"(d[102]), "+f"(d[103]), "+f"(d[104]), "+f"(d[105]), "+f"(d[106]), "+f"(d[107]), "+f"(d[108]), "+f"(d[109]), "+f"(d[110]), "+f"(d[111]), "+f"(d[112]), "+f"(d[113]), "+f"(d[114]), "+f"(d[115]), "+f"(d[116]), "+f"(d[117]), "+f"(d[118]), "+f"(d[119])
    : "l"(descA), "l"(descB), "r"(scaleD), "n"(TB));
}
template<int TB> __device__ __forceinline__ void wgmma_ss_n128(float (&d)[64], uint64_t descA, uint64_t descB, int scaleD) {
  asm volatile("{\n.reg .pred p;\nsetp.ne.b32 p, %66, 0;\n"
    "wgmma.mma_async.sync.aligned.m64n128k16.f32.bf16.bf16 {%0, %1, %2, %3, %4, %5, %6, %7, %8, %9, %10, %11, %12, %13, %14, %15, %16, %17, %18, %19, %20, %21, %22, %23, %24, %25, %26, %27, %28, %29, %30, %31, %32, %33, %34, %35, %36, %37, %38, %39, %40, %41, %42, %43, %44, %45, %46, %47, %48, %49, %50, %51, %52, %53, %54, %55, %56, %57, %58, %59, %60, %61, %62, %63}, %64, %65, p, 1, 1, 0, %67;\n}"
    : "+f"(d[0]), "+f"(d[1]), "+f"(d[2]), "+f"(d[3]), "+f"(d[4]), "+f"(d[5]), "+f"(d[6]), "+f"(d[7]), "+f"(d[8]), "+f"(d[9]), "+f"(d[10]), "+f"(d[11]), "+f"(d[12]), "+f"(d[13]), "+f"(d[14]), "+f"(d[15]), "+f"(d[16]), "+f"(d[17]), "+f"(d[18]), "+f"(d[19]), "+f"(d[20]), "+f"(d[21]), "+f"(d[22]), "+f"(d[23]), "+f"(d[24]), "+f"(d[25]), "+f"(d[26]), "+f"(d[27]), "+f"(d[28]), "+f"(d[29]), "+f"(d[30]), "+f"(d[31]), "+f"(d[32]), "+f"(d[33]), "+f"(d[34]), "+f"(d[35]), "+f"(d[36]), "+f"(d[37]), "+f"(d[38]), "+f"(d[39]), "+f"(d[40]), "+f"(d[41]), "+f"(d[42]), "+f"(d[43]), "+f"(d[44]), "+f"(d[45]), "+f"(d[46]), "+f"(d[47]), "+f"(d[48]), "+f"(d[49]), "+f"(d[50]), "+f"(d[51]), "+f"(d[52]), "+f"(d[53]), "+f"(d[54]), "+f"(d[55]), "+f"(d[56]), "+f"(d[57]), "+f"(d[58]), "+f"(d[59]), "+f"(d[60]), "+f"(d[61]), "+f"(d[62]), "+f"(d[63])
    : "l"(descA), "l"(descB), "r"(scaleD), "n"(TB));
}
template<int TB> __device__ __forceinline__ void wgmma_ss_n80(float (&d)[40], uint64_t descA, uint64_t descB, int scaleD) {
  asm volatile("{\n.reg .pred p;\nsetp.ne.b32 p, %42, 0;\n"
    "wgmma.mma_async.sync.aligned.m64n80k16.f32.bf16.bf16 {%0, %1, %2, %3, %4, %5, %6, %7, %8, %9, %10, %11, %12, %13, %14, %15, %16, %17, %18, %19, %20, %21, %22, %23, %24, %25, %26, %27, %28, %29, %30, %31, %32, %33, %34, %35, %36, %37, %38, %39}, %40, %41, p, 1, 1, 0, %43;\n}"
    : "+f"(d[0]), "+f"(d[1]), "+f"(d[2]), "+f"(d[3]), "+f"(d[4]), "+f"(d[5]), "+f"(d[6]), "+f"(d[7]), "+f"(d[8]), "+f"(d[9]), "+f"(d[10]), "+f"(d[11]), "+f"(d[12]), "+f"(d[13]), "+f"(d[14]), "+f"(d[15]), "+f"(d[16]), "+f"(d[17]), "+f"(d[18]), "+f"(d[19]), "+f"(d[20]), "+f"(d[21]), "+f"(d[22]), "+f"(d[23]), "+f"(d[24]), "+f"(d[25]), "+f"(d[26]), "+f"(d[27]), "+f"(d[28]), "+f"(d[29]), "+f"(d[30]), "+f"(d[31]), "+f"(d[32]), "+f"(d[33]), "+f"(d[34]), "+f"(d[35]), "+f"(d[36]), "+f"(d[37]), "+f"(d[38]), "+f"(d[39])
    : "l"(descA), "l"(descB), "r"(scaleD), "n"(TB));
}
template<int TB> __device__ __forceinline__ void wgmma_rs_n24(float (&d)[12], uint32_t a0, uint32_t a1, uint32_t a2, uint32_t a3, uint64_t descB, int scaleD) {
  asm volatile("{\n.reg .pred p;\nsetp.ne.b32 p, %17, 0;\n"
    "wgmma.mma_async.sync.aligned.m64n24k16.f32.bf16.bf16 {%0, %1, %2, %3, %4, %5, %6, %7, %8, %9, %10, %11}, {%12, %13, %14, %15}, %16, p, 1, 1, %18;\n}"
    : "+f"(d[0]), "+f"(d[1]), "+f"(d[2]), "+f"(d[3]), "+f"(d[4]), "+f"(d[5]), "+f"(d[6]), "+f"(d[7]), "+f"(d[8]), "+f"(d[9]), "+f"(d[10]), "+f"(d[11])
    : "r"(a0), "r"(a1), "r"(a2), "r"(a3), "l"(descB), "r"(scaleD), "n"(TB));
}


__device__ __forceinline__ void ln_prologue(const bf16* __restrict__ src, int row0, uint8_t* sA, int ctid) {
  const int warp = ctid >> 5, lane = ctid & 31;
  for (int rr = 0; rr < 16; rr += 8) {
    uint2 v[8][5];
#pragma unroll
    for (int u = 0; u < 8; u++) {
      const uint2* p = reinterpret_cast<const uint2*>(src + (size_t)(row0 + warp * 16 + rr + u) * DM);
#pragma unroll
      for (int j = 0; j < 5; j++) v[u][j] = p[lane + 32 * j];
    }
#pragma unroll
    for (int u = 0; u < 8; u++) {
      float f[20];
#pragma unroll
      for (int j = 0; j < 5; j++) {
        f[4 * j + 0] = __uint_as_float(v[u][j].x << 16);
        f[4 * j + 1] = __uint_as_float(v[u][j].x & 0xffff0000u);
        f[4 * j + 2] = __uint_as_float(v[u][j].y << 16);
        f[4 * j + 3] = __uint_as_float(v[u][j].y & 0xffff0000u);
      }
      float s = 0.f;
#pragma unroll
      for (int j = 0; j < 20; j++) s += f[j];
#pragma unroll
      for (int o = 16; o > 0; o >>= 1) s += __shfl_xor_sync(0xffffffffu, s, o);
      const float mean = s * (1.0f / DM);
      float q = 0.f;
#pragma unroll
      for (int j = 0; j < 20; j++) { f[j] -= mean; q += f[j] * f[j]; }
#pragma unroll
      for (int o = 16; o > 0; o >>= 1) q += __shfl_xor_sync(0xffffffffu, q, o);
      const float rstd = rsqrtf(q * (1.0f / DM) + 1e-5f);
      const int r = warp * 16 + rr + u;
#pragma unroll
      for (int j = 0; j < 5; j++) {
        const int e = (lane + 32 * j) * 4;
        const int kb = e >> 6;
        const int byte = (e & 63) * 2;
        const int chunk = byte >> 4;
        const int sw = ((chunk ^ (r & 7)) << 4) | (byte & 15);
        uint2 o;
        o.x = pack_bf16(f[4 * j + 0] * rstd, f[4 * j + 1] * rstd);
        o.y = pack_bf16(f[4 * j + 2] * rstd, f[4 * j + 3] * rstd);
        *reinterpret_cast<uint2*>(sA + kb * 16384 + r * 128 + sw) = o;
      }
    }
  }
}

constexpr int K1_STAGES = 4;
constexpr int K1_SMEM = 163840 + K1_STAGES * 16384 + 1024;
__global__ void __launch_bounds__(288, 1) k1_ln_qkv(const bf16* __restrict__ x, const __grid_constant__ CUtensorMap tmW) {
  extern __shared__ __align__(1024) uint8_t smem[];
  uint8_t* sA = smem;
  uint8_t* sB = smem + 163840;
  const uint32_t bar0 = smem_u32(smem + 163840 + K1_STAGES * 16384);
  const int tid = threadIdx.x;
  const int mblk = blockIdx.x >> 3, nblk = blockIdx.x & 7;
  if (tid == 0) {
    for (int s = 0; s < K1_STAGES; s++) { mbar_init(bar0 + 8 * s, 1); mbar_init(bar0 + 64 + 8 * s, 2); }
    asm volatile("fence.mbarrier_init.release.cluster;" ::: "memory");
  }
  __syncthreads();
  if (tid >= 256) {
    if (tid == 256) {
      for (int it = 0; it < 20; it++) {
        const int s = it % K1_STAGES;
        mbar_wait(bar0 + 64 + 8 * s, ((it / K1_STAGES) & 1) ^ 1);
        mbar_expect_tx(bar0 + 8 * s, 16384);
        for (int b = 0; b < 4; b++)
          tma_load_2d(smem_u32(sB + s * 16384 + b * 4096), &tmW, nblk * 240 + b * 64, it * 32, bar0 + 8 * s);
      }
    }
    return;
  }
  ln_prologue(x, mblk * 128, sA, tid);
  fence_async_smem();
  named_bar_sync(1, 256);
  const int wg = tid >> 7;
  float acc[120];
#pragma unroll
  for (int i = 0; i < 120; i++) acc[i] = 0.f;
  const uint32_t aBase = smem_u32(sA) + wg * 64 * 128;
  const uint32_t bBase = smem_u32(sB);
  for (int it = 0; it < 20; it++) {
    const int s = it % K1_STAGES;
    mbar_wait(bar0 + 8 * s, (it / K1_STAGES) & 1);
    wg_fence();
#pragma unroll
    for (int kk = 0; kk < 2; kk++) {
      uint64_t da = make_desc(aBase + (it >> 1) * 16384 + (it & 1) * 64 + kk * 32, 16, 1024, 1);
      uint64_t db = make_desc(bBase + s * 16384 + kk * 2048, 4096, 1024, 1);
      wgmma_ss_n240<1>(acc, da, db, 1);
    }
    wg_commit();
    wg_wait<1>();
    if (it > 0 && (tid & 127) == 0) mbar_arrive(bar0 + 64 + 8 * ((it - 1) % K1_STAGES));
  }
  wg_wait<0>();
  reg_fence(acc);
  const int lane = tid & 31, q = lane & 3;
  const int row = mblk * 128 + wg * 64 + ((tid & 127) >> 5) * 16 + (lane >> 2);
#pragma unroll
  for (int i = 0; i < 30; i++) {
    const int col = 8 * i + 2 * q;
    const int sl = col / 20, d = col - sl * 20;
    const size_t base = ((size_t)(nblk * 12 + sl) * SEQ + row) * 32 + d;
    *reinterpret_cast<uint32_t*>(g_qkv + base) = pack_bf16(acc[4 * i], acc[4 * i + 1]);
    *reinterpret_cast<uint32_t*>(g_qkv + base + 8 * 32) = pack_bf16(acc[4 * i + 2], acc[4 * i + 3]);
  }
  for (int t = tid; t < 128 * 12 * 3; t += 256) {
    const int part = t % 3, sl = (t / 3) % 12, r = t / 36;
    const int gs = nblk * 12 + sl;
    uint2 val = make_uint2(0u, 0u);
    if (gs >= 64 && part == 0) val.x = 0x00003F80u;
    *reinterpret_cast<uint2*>(g_qkv + ((size_t)gs * SEQ + mblk * 128 + r) * 32 + 20 + part * 4) = val;
  }
}

constexpr int K2_STAGES = 6;
constexpr int K2_SMEM = 16384 + K2_STAGES * 16384 + 1024;
__global__ void __launch_bounds__(512, 1) k2_attn(const __grid_constant__ CUtensorMap tmQKV) {
  extern __shared__ __align__(1024) uint8_t smem[];
  uint8_t* sQ = smem;
  uint8_t* sKV = smem + 16384;
  const uint32_t bar0 = smem_u32(smem + 16384 + K2_STAGES * 16384);
  const int tid = threadIdx.x;
  const int head = blockIdx.x >> 3, qblk = blockIdx.x & 7;
  if (tid == 0) {
    for (int s = 0; s < K2_STAGES; s++) { mbar_init(bar0 + 8 * s, 1); mbar_init(bar0 + 64 + 8 * s, 4); }
    mbar_init(bar0 + 128, 1);
    asm volatile("fence.mbarrier_init.release.cluster;" ::: "memory");
  }
  __syncthreads();
  if (tid == 0) {
    mbar_expect_tx(bar0 + 128, 16384);
    tma_load_2d(smem_u32(sQ), &tmQKV, 0, head * SEQ + qblk * 256, bar0 + 128);
    tma_load_2d(smem_u32(sQ) + 8192, &tmQKV, 0, head * SEQ + qblk * 256 + 128, bar0 + 128);
    for (int it = 0; it < K2_STAGES - 1; it++) {
      mbar_expect_tx(bar0 + 8 * it, 16384);
      tma_load_2d(smem_u32(sKV + it * 16384), &tmQKV, 0, (32 + head) * SEQ + it * 128, bar0 + 8 * it);
      tma_load_2d(smem_u32(sKV + it * 16384 + 8192), &tmQKV, 0, (64 + head) * SEQ + it * 128, bar0 + 8 * it);
    }
  }
  const int wg = tid >> 7, lane = tid & 31;
  const float c = 0.22360679774997896f * 1.4426950408889634f;
  float o[12];
#pragma unroll
  for (int i = 0; i < 12; i++) o[i] = 0.f;
  float m0 = -INFINITY, m1 = -INFINITY;
  const uint32_t qBase = smem_u32(sQ) + wg * 4096;
  mbar_wait(bar0 + 128, 0);
  for (int it = 0; it < 16; it++) {
    const int s = it % K2_STAGES;
    const uint32_t kBase = smem_u32(sKV + s * 16384), vBase = kBase + 8192;
    float sc[64];
    if (tid == 0 && it + K2_STAGES - 1 < 16) {
      const int n = it + K2_STAGES - 1, ns = n % K2_STAGES;
      mbar_wait(bar0 + 64 + 8 * ns, ((n / K2_STAGES) & 1) ^ 1);
      mbar_expect_tx(bar0 + 8 * ns, 16384);
      tma_load_2d(smem_u32(sKV + ns * 16384), &tmQKV, 0, (32 + head) * SEQ + n * 128, bar0 + 8 * ns);
      tma_load_2d(smem_u32(sKV + ns * 16384 + 8192), &tmQKV, 0, (64 + head) * SEQ + n * 128, bar0 + 8 * ns);
    }
    __syncwarp();
    mbar_wait(bar0 + 8 * s, (it / K2_STAGES) & 1);
    wg_fence();
#pragma unroll
    for (int kk = 0; kk < 2; kk++)
      wgmma_ss_n128<0>(sc, make_desc(qBase + kk * 32, 16, 512, 2), make_desc(kBase + kk * 32, 16, 512, 2), kk);
    wg_commit();
    wg_wait<0>();
    reg_fence(sc);
    float mx0 = m0, mx1 = m1;
#pragma unroll
    for (int i = 0; i < 16; i++) {
      mx0 = fmaxf(mx0, fmaxf(sc[4 * i], sc[4 * i + 1]));
      mx1 = fmaxf(mx1, fmaxf(sc[4 * i + 2], sc[4 * i + 3]));
    }
    mx0 = fmaxf(mx0, __shfl_xor_sync(0xffffffffu, mx0, 1)); mx0 = fmaxf(mx0, __shfl_xor_sync(0xffffffffu, mx0, 2));
    mx1 = fmaxf(mx1, __shfl_xor_sync(0xffffffffu, mx1, 1)); mx1 = fmaxf(mx1, __shfl_xor_sync(0xffffffffu, mx1, 2));
    const float a0 = ex2((m0 - mx0) * c), a1 = ex2((m1 - mx1) * c);
    m0 = mx0; m1 = mx1;
    const float nb0 = -mx0 * c, nb1 = -mx1 * c;
    uint32_t p[32];
#pragma unroll
    for (int i = 0; i < 16; i++) {
      p[2 * i] = pack_bf16(ex2(fmaf(sc[4 * i], c, nb0)), ex2(fmaf(sc[4 * i + 1], c, nb0)));
      p[2 * i + 1] = pack_bf16(ex2(fmaf(sc[4 * i + 2], c, nb1)), ex2(fmaf(sc[4 * i + 3], c, nb1)));
    }
#pragma unroll
    for (int i = 0; i < 3; i++) { o[4 * i] *= a0; o[4 * i + 1] *= a0; o[4 * i + 2] *= a1; o[4 * i + 3] *= a1; }
    wg_fence();
#pragma unroll
    for (int kk = 0; kk < 8; kk++)
      wgmma_rs_n24<1>(o, p[4 * kk], p[4 * kk + 1], p[4 * kk + 2], p[4 * kk + 3], make_desc(vBase + kk * 1024, 16, 512, 2), 1);
    wg_commit();
    wg_wait<0>();
    reg_fence(o);
    if ((tid & 127) == 0) mbar_arrive(bar0 + 64 + 8 * s);
  }
  const float l0 = __shfl_sync(0xffffffffu, o[8], (lane & ~3) | 2);
  const float l1 = __shfl_sync(0xffffffffu, o[10], (lane & ~3) | 2);
  const float i0 = 1.0f / l0, i1 = 1.0f / l1;
  const int q = lane & 3;
  const int row = qblk * 256 + wg * 64 + ((tid & 127) >> 5) * 16 + (lane >> 2);
#pragma unroll
  for (int i = 0; i < 3; i++) {
    const int d = 8 * i + 2 * q;
    if (d < 20) {
      *reinterpret_cast<uint32_t*>(g_o + (size_t)row * DM + head * 20 + d) = pack_bf16(o[4 * i] * i0, o[4 * i + 1] * i0);
      *reinterpret_cast<uint32_t*>(g_o + (size_t)(row + 8) * DM + head * 20 + d) = pack_bf16(o[4 * i + 2] * i1, o[4 * i + 3] * i1);
    }
  }
}

constexpr int G_STAGES = 6;
constexpr int G_STAGE_BYTES = 16384 + 16384;
constexpr int G_SMEM = G_STAGES * G_STAGE_BYTES + 1024;
template <int KTOT>
__global__ void __launch_bounds__(288, 1) k_gemm_res(const __grid_constant__ CUtensorMap tmA, const __grid_constant__ CUtensorMap tmB,
                                                     const bf16* __restrict__ res, bf16* __restrict__ out) {
  extern __shared__ __align__(1024) uint8_t smem[];
  const uint32_t bar0 = smem_u32(smem + G_STAGES * G_STAGE_BYTES);
  const int tid = threadIdx.x;
  const int mblk = blockIdx.x >> 3, nblk = blockIdx.x & 7;
  constexpr int NIT = KTOT / 64;
  if (tid == 0) {
    for (int s = 0; s < G_STAGES; s++) { mbar_init(bar0 + 8 * s, 1); mbar_init(bar0 + 64 + 8 * s, 2); }
    asm volatile("fence.mbarrier_init.release.cluster;" ::: "memory");
  }
  __syncthreads();
  if (tid >= 256) {
    if (tid == 256) {
      for (int it = 0; it < NIT; it++) {
        const int s = it % G_STAGES;
        mbar_wait(bar0 + 64 + 8 * s, ((it / G_STAGES) & 1) ^ 1);
        mbar_expect_tx(bar0 + 8 * s, G_STAGE_BYTES);
        const uint32_t st = smem_u32(smem + s * G_STAGE_BYTES);
        tma_load_2d(st, &tmA, it * 64, mblk * 128, bar0 + 8 * s);
        tma_load_2d(st + 16384, &tmB, nblk * 80, it * 64, bar0 + 8 * s);
        tma_load_2d(st + 16384 + 8192, &tmB, nblk * 80 + 64, it * 64, bar0 + 8 * s);
      }
    }
    return;
  }
  const int wg = tid >> 7;
  float acc[40];
#pragma unroll
  for (int i = 0; i < 40; i++) acc[i] = 0.f;
  for (int it = 0; it < NIT; it++) {
    const int s = it % G_STAGES;
    const uint32_t st = smem_u32(smem + s * G_STAGE_BYTES);
    mbar_wait(bar0 + 8 * s, (it / G_STAGES) & 1);
    wg_fence();
#pragma unroll
    for (int kk = 0; kk < 4; kk++) {
      uint64_t da = make_desc(st + wg * 8192 + kk * 32, 16, 1024, 1);
      uint64_t db = make_desc(st + 16384 + kk * 2048, 8192, 1024, 1);
      wgmma_ss_n80<1>(acc, da, db, 1);
    }
    wg_commit();
    wg_wait<1>();
    if (it > 0 && (tid & 127) == 0) mbar_arrive(bar0 + 64 + 8 * ((it - 1) % G_STAGES));
  }
  wg_wait<0>();
  reg_fence(acc);
  const int lane = tid & 31, q = lane & 3;
  const int row = mblk * 128 + wg * 64 + ((tid & 127) >> 5) * 16 + (lane >> 2);
#pragma unroll
  for (int i = 0; i < 10; i++) {
    const int col = nblk * 80 + 8 * i + 2 * q;
    const uint32_t r0 = *reinterpret_cast<const uint32_t*>(res + (size_t)row * DM + col);
    const uint32_t r1 = *reinterpret_cast<const uint32_t*>(res + (size_t)(row + 8) * DM + col);
    *reinterpret_cast<uint32_t*>(out + (size_t)row * DM + col) =
        pack_bf16(acc[4 * i] + __uint_as_float(r0 << 16), acc[4 * i + 1] + __uint_as_float(r0 & 0xffff0000u));
    *reinterpret_cast<uint32_t*>(out + (size_t)(row + 8) * DM + col) =
        pack_bf16(acc[4 * i + 2] + __uint_as_float(r1 << 16), acc[4 * i + 3] + __uint_as_float(r1 & 0xffff0000u));
  }
}

constexpr int K4_STAGES = 4;
constexpr int K4_SMEM = 163840 + K4_STAGES * 16384 + 1024;
__global__ void __launch_bounds__(288, 1) k4_ln_ffn(const __grid_constant__ CUtensorMap tmG, const __grid_constant__ CUtensorMap tmU) {
  extern __shared__ __align__(1024) uint8_t smem[];
  uint8_t* sA = smem;
  uint8_t* sB = smem + 163840;
  const uint32_t bar0 = smem_u32(smem + 163840 + K4_STAGES * 16384);
  const int tid = threadIdx.x;
  const int mblk = blockIdx.x >> 3, nblk = blockIdx.x & 7;
  if (tid == 0) {
    for (int s = 0; s < K4_STAGES; s++) { mbar_init(bar0 + 8 * s, 1); mbar_init(bar0 + 64 + 8 * s, 2); }
    asm volatile("fence.mbarrier_init.release.cluster;" ::: "memory");
  }
  __syncthreads();
  if (tid >= 256) {
    if (tid == 256) {
      for (int it = 0; it < 30; it++) {
        const int s = it % K4_STAGES;
        const int pass = it / 10, kb = it % 10;
        mbar_wait(bar0 + 64 + 8 * s, ((it / K4_STAGES) & 1) ^ 1);
        mbar_expect_tx(bar0 + 8 * s, 16384);
        tma_load_2d(smem_u32(sB + s * 16384), &tmG, nblk * 192 + pass * 64, kb * 64, bar0 + 8 * s);
        tma_load_2d(smem_u32(sB + s * 16384 + 8192), &tmU, nblk * 192 + pass * 64, kb * 64, bar0 + 8 * s);
      }
    }
    return;
  }
  ln_prologue(g_h, mblk * 128, sA, tid);
  fence_async_smem();
  named_bar_sync(1, 256);
  const int wg = tid >> 7;
  const uint32_t aBase = smem_u32(sA) + wg * 64 * 128;
  const uint32_t bBase = smem_u32(sB);
  const int lane = tid & 31, q = lane & 3;
  const int row = mblk * 128 + wg * 64 + ((tid & 127) >> 5) * 16 + (lane >> 2);
  for (int pass = 0; pass < 3; pass++) {
    float acc[64];
#pragma unroll
    for (int i = 0; i < 64; i++) acc[i] = 0.f;
    for (int kb = 0; kb < 10; kb++) {
      const int it = pass * 10 + kb;
      const int s = it % K4_STAGES;
      mbar_wait(bar0 + 8 * s, (it / K4_STAGES) & 1);
      wg_fence();
#pragma unroll
      for (int kk = 0; kk < 4; kk++) {
        uint64_t da = make_desc(aBase + kb * 16384 + kk * 32, 16, 1024, 1);
        uint64_t db = make_desc(bBase + s * 16384 + kk * 2048, 8192, 1024, 1);
        wgmma_ss_n128<1>(acc, da, db, 1);
      }
      wg_commit();
      wg_wait<1>();
      if (kb > 0 && (tid & 127) == 0) mbar_arrive(bar0 + 64 + 8 * ((it - 1) % K4_STAGES));
    }
    wg_wait<0>();
    if ((tid & 127) == 0) mbar_arrive(bar0 + 64 + 8 * ((pass * 10 + 9) % K4_STAGES));
    reg_fence(acc);
#pragma unroll
    for (int i = 0; i < 8; i++) {
      const int col = nblk * 192 + pass * 64 + 8 * i + 2 * q;
      float r[4];
#pragma unroll
      for (int j = 0; j < 4; j++) {
        const float g = acc[4 * i + j], u = acc[32 + 4 * i + j];
        r[j] = g / (1.0f + __expf(-g)) * u;
      }
      *reinterpret_cast<uint32_t*>(g_act + (size_t)row * FF + col) = pack_bf16(r[0], r[1]);
      *reinterpret_cast<uint32_t*>(g_act + (size_t)(row + 8) * FF + col) = pack_bf16(r[2], r[3]);
    }
  }
}

typedef CUresult (*EncodeFn)(CUtensorMap*, CUtensorMapDataType, cuuint32_t, void*, const cuuint64_t*, const cuuint64_t*,
                             const cuuint32_t*, const cuuint32_t*, CUtensorMapInterleave, CUtensorMapSwizzle,
                             CUtensorMapL2promotion, CUtensorMapFloatOOBfill);
static void make_map(EncodeFn fn, CUtensorMap* m, const void* ptr, uint64_t cols, uint64_t rows, uint32_t bc, uint32_t br,
                     CUtensorMapSwizzle sw) {
  cuuint64_t dims[2] = {cols, rows};
  cuuint64_t strides[1] = {cols * 2};
  cuuint32_t box[2] = {bc, br};
  cuuint32_t es[2] = {1, 1};
  fn(m, CU_TENSOR_MAP_DATA_TYPE_BFLOAT16, 2, const_cast<void*>(ptr), dims, strides, box, es, CU_TENSOR_MAP_INTERLEAVE_NONE, sw,
     CU_TENSOR_MAP_L2_PROMOTION_L2_128B, CU_TENSOR_MAP_FLOAT_OOB_FILL_NONE);
}

extern "C" void kernel_launch(void* const* d_in, const int* in_sizes, int n_in, void* d_out, int out_size) {
  const bf16* x = (const bf16*)d_in[0];
  const bf16* wqkv = (const bf16*)d_in[1];
  const bf16* wo = (const bf16*)d_in[2];
  const bf16* wg = (const bf16*)d_in[4];
  const bf16* wu = (const bf16*)d_in[5];
  const bf16* wd = (const bf16*)d_in[6];
  bf16* out = (bf16*)d_out;
  static EncodeFn fn = nullptr;
  static void *p_qkv, *p_o, *p_h, *p_act;
  if (!fn) {
    void* f = nullptr;
    cudaDriverEntryPointQueryResult qr;
    cudaGetDriverEntryPoint("cuTensorMapEncodeTiled", &f, cudaEnableDefault, &qr);
    fn = (EncodeFn)f;
    cudaGetSymbolAddress(&p_qkv, g_qkv);
    cudaGetSymbolAddress(&p_o, g_o);
    cudaGetSymbolAddress(&p_h, g_h);
    cudaGetSymbolAddress(&p_act, g_act);
    cudaFuncSetAttribute(k1_ln_qkv, cudaFuncAttributeMaxDynamicSharedMemorySize, K1_SMEM);
    cudaFuncSetAttribute(k2_attn, cudaFuncAttributeMaxDynamicSharedMemorySize, K2_SMEM);
    cudaFuncSetAttribute(k_gemm_res<640>, cudaFuncAttributeMaxDynamicSharedMemorySize, G_SMEM);
    cudaFuncSetAttribute(k_gemm_res<1536>, cudaFuncAttributeMaxDynamicSharedMemorySize, G_SMEM);
    cudaFuncSetAttribute(k4_ln_ffn, cudaFuncAttributeMaxDynamicSharedMemorySize, K4_SMEM);
  }
  CUtensorMap mWqkv, mQKV, mO, mWo, mWg, mWu, mAct, mWd;
  make_map(fn, &mWqkv, wqkv, 3 * DM, DM, 64, 32, CU_TENSOR_MAP_SWIZZLE_128B);
  make_map(fn, &mQKV, p_qkv, 32, 3 * NH * SEQ, 32, 128, CU_TENSOR_MAP_SWIZZLE_64B);
  make_map(fn, &mO, p_o, DM, SEQ, 64, 128, CU_TENSOR_MAP_SWIZZLE_128B);
  make_map(fn, &mWo, wo, DM, DM, 64, 64, CU_TENSOR_MAP_SWIZZLE_128B);
  make_map(fn, &mWg, wg, FF, DM, 64, 64, CU_TENSOR_MAP_SWIZZLE_128B);
  make_map(fn, &mWu, wu, FF, DM, 64, 64, CU_TENSOR_MAP_SWIZZLE_128B);
  make_map(fn, &mAct, p_act, FF, SEQ, 64, 128, CU_TENSOR_MAP_SWIZZLE_128B);
  make_map(fn, &mWd, wd, DM, FF, 64, 64, CU_TENSOR_MAP_SWIZZLE_128B);
  k1_ln_qkv<<<128, 288, K1_SMEM>>>(x, mWqkv);
  k2_attn<<<256, 512, K2_SMEM>>>(mQKV);
  k_gemm_res<640><<<128, 288, G_SMEM>>>(mO, mWo, x, (bf16*)p_h);
  k4_ln_ffn<<<128, 288, K4_SMEM>>>(mWg, mWu);
  k_gemm_res<1536><<<128, 288, G_SMEM>>>(mAct, mWd, (const bf16*)p_h, out);
}
```

```cpp
#include <cuda_runtime.h>
#include <cuda_bf16.h>
#include <cuda.h>
#include <stdint.h>

typedef __nv_bfloat16 bf16;

constexpr int SEQ = 2048, DM = 640, NH = 32, DH = 20, FF = 1536;

__device__ __align__(1024) bf16 g_qkv[3 * NH * SEQ * 32];
__device__ __align__(1024) bf16 g_o[SEQ * DM];
__device__ __align__(1024) bf16 g_h[SEQ * DM];
__device__ __align__(1024) bf16 g_act[SEQ * FF];

__device__ __forceinline__ uint32_t smem_u32(const void* p) { return (uint32_t)__cvta_generic_to_shared(p); }
__device__ __forceinline__ void mbar_init(uint32_t bar, uint32_t count) {
  asm volatile("mbarrier.init.shared::cta.b64 [%0], %1;" :: "r"(bar), "r"(count) : "memory");
}
__device__ __forceinline__ void mbar_expect_tx(uint32_t bar, uint32_t bytes) {
  asm volatile("mbarrier.arrive.expect_tx.shared::cta.b64 _, [%0], %1;" :: "r"(bar), "r"(bytes) : "memory");
}
__device__ __forceinline__ void mbar_arrive(uint32_t bar) {
  asm volatile("mbarrier.arrive.shared::cta.b64 _, [%0];" :: "r"(bar) : "memory");
}
__device__ __forceinline__ void mbar_wait(uint32_t bar, uint32_t parity) {
  uint32_t done;
  uint32_t it = 0;
  do {
    asm volatile("{\n.reg .pred p;\nmbarrier.try_wait.parity.shared::cta.b64 p, [%1], %2;\nselp.u32 %0, 1, 0, p;\n}"
                 : "=r"(done) : "r"(bar), "r"(parity) : "memory");
    if (++it > 4000000u) __trap();
  } while (!done);
}
__device__ __forceinline__ void tma_load_2d(uint32_t dst, const CUtensorMap* map, int c0, int c1, uint32_t bar) {
  asm volatile("cp.async.bulk.tensor.2d.shared::cluster.global.mbarrier::complete_tx::bytes [%0], [%1, {%3, %4}], [%2];"
               :: "r"(dst), "l"((uint64_t)map), "r"(bar), "r"(c0), "r"(c1) : "memory");
}
__device__ __forceinline__ void fence_async_smem() { asm volatile("fence.proxy.async.shared::cta;" ::: "memory"); }
__device__ __forceinline__ void wg_fence() { asm volatile("wgmma.fence.sync.aligned;" ::: "memory"); }
__device__ __forceinline__ void wg_commit() { asm volatile("wgmma.commit_group.sync.aligned;" ::: "memory"); }
template <int N> __device__ __forceinline__ void wg_wait() { asm volatile("wgmma.wait_group.sync.aligned %0;" :: "n"(N) : "memory"); }
template <int N> __device__ __forceinline__ void reg_fence(float (&d)[N]) {
#pragma unroll
  for (int i = 0; i < N; i++) asm volatile("" : "+f"(d[i]) :: "memory");
}
__device__ __forceinline__ uint64_t make_desc(uint32_t addr, uint32_t lbo, uint32_t sbo, uint32_t swz) {
  return (uint64_t)((addr & 0x3FFFF) >> 4) | ((uint64_t)(lbo >> 4) << 16) | ((uint64_t)(sbo >> 4) << 32) | ((uint64_t)swz << 62);
}
__device__ __forceinline__ uint32_t pack_bf16(float a, float b) {
  __nv_bfloat162 v = __floats2bfloat162_rn(a, b);
  return *reinterpret_cast<uint32_t*>(&v);
}
__device__ __forceinline__ float ex2(float x) { float y; asm("ex2.approx.ftz.f32 %0, %1;" : "=f"(y) : "f"(x)); return y; }
__device__ __forceinline__ void named_bar_sync(int id, int n) { asm volatile("bar.sync %0, %1;" :: "r"(id), "r"(n) : "memory"); }

template<int TB> __device__ __forceinline__ void wgmma_ss_n240(float (&d)[120], uint64_t descA, uint64_t descB, int scaleD) {
  asm volatile("{\n.reg .pred p;\nsetp.ne.b32 p, %122, 0;\n"
    "wgmma.mma_async.sync.aligned.m64n240k16.f32.bf16.bf16 {%0, %1, %2, %3, %4, %5, %6, %7, %8, %9, %10, %11, %12, %13, %14, %15, %16, %17, %18, %19, %20, %21, %22, %23, %24, %25, %26, %27, %28, %29, %30, %31, %32, %33, %34, %35, %36, %37, %38, %39, %40, %41, %42, %43, %44, %45, %46, %47, %48, %49, %50, %51, %52, %53, %54, %55, %56, %57, %58, %59, %60, %61, %62, %63, %64, %65, %66, %67, %68, %69, %70, %71, %72, %73, %74, %75, %76, %77, %78, %79, %80, %81, %82, %83, %84, %85, %86, %87, %88, %89, %90, %91, %92, %93, %94, %95, %96, %97, %98, %99, %100, %101, %102, %103, %104, %105, %106, %107, %108, %109, %110, %111, %112, %113, %114, %115, %116, %117, %118, %119}, %120, %121, p, 1, 1, 0, %123;\n}"
    : "+f"(d[0]), "+f"(d[1]), "+f"(d[2]), "+f"(d[3]), "+f"(d[4]), "+f"(d[5]), "+f"(d[6]), "+f"(d[7]), "+f"(d[8]), "+f"(d[9]), "+f"(d[10]), "+f"(d[11]), "+f"(d[12]), "+f"(d[13]), "+f"(d[14]), "+f"(d[15]), "+f"(d[16]), "+f"(d[17]), "+f"(d[18]), "+f"(d[19]), "+f"(d[20]), "+f"(d[21]), "+f"(d[22]), "+f"(d[23]), "+f"(d[24]), "+f"(d[25]), "+f"(d[26]), "+f"(d[27]), "+f"(d[28]), "+f"(d[29]), "+f"(d[30]), "+f"(d[31]), "+f"(d[32]), "+f"(d[33]), "+f"(d[34]), "+f"(d[35]), "+f"(d[36]), "+f"(d[37]), "+f"(d[38]), "+f"(d[39]), "+f"(d[40]), "+f"(d[41]), "+f"(d[42]), "+f"(d[43]), "+f"(d[44]), "+f"(d[45]), "+f"(d[46]), "+f"(d[47]), "+f"(d[48]), "+f"(d[49]), "+f"(d[50]), "+f"(d[51]), "+f"(d[52]), "+f"(d[53]), "+f"(d[54]), "+f"(d[55]), "+f"(d[56]), "+f"(d[57]), "+f"(d[58]), "+f"(d[59]), "+f"(d[60]), "+f"(d[61]), "+f"(d[62]), "+f"(d[63]), "+f"(d[64]), "+f"(d[65]), "+f"(d[66]), "+f"(d[67]), "+f"(d[68]), "+f"(d[69]), "+f"(d[70]), "+f"(d[71]), "+f"(d[72]), "+f"(d[73]), "+f"(d[74]), "+f"(d[75]), "+f"(d[76]), "+f"(d[77]), "+f"(d[78]), "+f"(d[79]), "+f"(d[80]), "+f"(d[81]), "+f"(d[82]), "+f"(d[83]), "+f"(d[84]), "+f"(d[85]), "+f"(d[86]), "+f"(d[87]), "+f"(d[88]), "+f"(d[89]), "+f"(d[90]), "+f"(d[91]), "+f"(d[92]), "+f"(d[93]), "+f"(d[94]), "+f"(d[95]), "+f"(d[96]), "+f"(d[97]), "+f"(d[98]), "+f"(d[99]), "+f"(d[100]), "+f"(d[101]), "+f"(d[102]), "+f"(d[103]), "+f"(d[104]), "+f"(d[105]), "+f"(d[106]), "+f"(d[107]), "+f"(d[108]), "+f"(d[109]), "+f"(d[110]), "+f"(d[111]), "+f"(d[112]), "+f"(d[113]), "+f"(d[114]), "+f"(d[115]), "+f"(d[116]), "+f"(d[117]), "+f"(d[118]), "+f"(d[119])
    : "l"(descA), "l"(descB), "r"(scaleD), "n"(TB));
}
template<int TB> __device__ __forceinline__ void wgmma_ss_n128(float (&d)[64], uint64_t descA, uint64_t descB, int scaleD) {
  asm volatile("{\n.reg .pred p;\nsetp.ne.b32 p, %66, 0;\n"
    "wgmma.mma_async.sync.aligned.m64n128k16.f32.bf16.bf16 {%0, %1, %2, %3, %4, %5, %6, %7, %8, %9, %10, %11, %12, %13, %14, %15, %16, %17, %18, %19, %20, %21, %22, %23, %24, %25, %26, %27, %28, %29, %30, %31, %32, %33, %34, %35, %36, %37, %38, %39, %40, %41, %42, %43, %44, %45, %46, %47, %48, %49, %50, %51, %52, %53, %54, %55, %56, %57, %58, %59, %60, %61, %62, %63}, %64, %65, p, 1, 1, 0, %67;\n}"
    : "+f"(d[0]), "+f"(d[1]), "+f"(d[2]), "+f"(d[3]), "+f"(d[4]), "+f"(d[5]), "+f"(d[6]), "+f"(d[7]), "+f"(d[8]), "+f"(d[9]), "+f"(d[10]), "+f"(d[11]), "+f"(d[12]), "+f"(d[13]), "+f"(d[14]), "+f"(d[15]), "+f"(d[16]), "+f"(d[17]), "+f"(d[18]), "+f"(d[19]), "+f"(d[20]), "+f"(d[21]), "+f"(d[22]), "+f"(d[23]), "+f"(d[24]), "+f"(d[25]), "+f"(d[26]), "+f"(d[27]), "+f"(d[28]), "+f"(d[29]), "+f"(d[30]), "+f"(d[31]), "+f"(d[32]), "+f"(d[33]), "+f"(d[34]), "+f"(d[35]), "+f"(d[36]), "+f"(d[37]), "+f"(d[38]), "+f"(d[39]), "+f"(d[40]), "+f"(d[41]), "+f"(d[42]), "+f"(d[43]), "+f"(d[44]), "+f"(d[45]), "+f"(d[46]), "+f"(d[47]), "+f"(d[48]), "+f"(d[49]), "+f"(d[50]), "+f"(d[51]), "+f"(d[52]), "+f"(d[53]), "+f"(d[54]), "+f"(d[55]), "+f"(d[56]), "+f"(d[57]), "+f"(d[58]), "+f"(d[59]), "+f"(d[60]), "+f"(d[61]), "+f"(d[62]), "+f"(d[63])
    : "l"(descA), "l"(descB), "r"(scaleD), "n"(TB));
}
template<int TB> __device__ __forceinline__ void wgmma_ss_n80(float (&d)[40], uint64_t descA, uint64_t descB, int scaleD) {
  asm volatile("{\n.reg .pred p;\nsetp.ne.b32 p, %42, 0;\n"
    "wgmma.mma_async.sync.aligned.m64n80k16.f32.bf16.bf16 {%0, %1, %2, %3, %4, %5, %6, %7, %8, %9, %10, %11, %12, %13, %14, %15, %16, %17, %18, %19, %20, %21, %22, %23, %24, %25, %26, %27, %28, %29, %30, %31, %32, %33, %34, %35, %36, %37, %38, %39}, %40, %41, p, 1, 1, 0, %43;\n}"
    : "+f"(d[0]), "+f"(d[1]), "+f"(d[2]), "+f"(d[3]), "+f"(d[4]), "+f"(d[5]), "+f"(d[6]), "+f"(d[7]), "+f"(d[8]), "+f"(d[9]), "+f"(d[10]), "+f"(d[11]), "+f"(d[12]), "+f"(d[13]), "+f"(d[14]), "+f"(d[15]), "+f"(d[16]), "+f"(d[17]), "+f"(d[18]), "+f"(d[19]), "+f"(d[20]), "+f"(d[21]), "+f"(d[22]), "+f"(d[23]), "+f"(d[24]), "+f"(d[25]), "+f"(d[26]), "+f"(d[27]), "+f"(d[28]), "+f"(d[29]), "+f"(d[30]), "+f"(d[31]), "+f"(d[32]), "+f"(d[33]), "+f"(d[34]), "+f"(d[35]), "+f"(d[36]), "+f"(d[37]), "+f"(d[38]), "+f"(d[39])
    : "l"(descA), "l"(descB), "r"(scaleD), "n"(TB));
}
template<int TB> __device__ __forceinline__ void wgmma_rs_n24(float (&d)[12], uint32_t a0, uint32_t a1, uint32_t a2, uint32_t a3, uint64_t descB, int scaleD) {
  asm volatile("{\n.reg .pred p;\nsetp.ne.b32 p, %17, 0;\n"
    "wgmma.mma_async.sync.aligned.m64n24k16.f32.bf16.bf16 {%0, %1, %2, %3, %4, %5, %6, %7, %8, %9, %10, %11}, {%12, %13, %14, %15}, %16, p, 1, 1, %18;\n}"
    : "+f"(d[0]), "+f"(d[1]), "+f"(d[2]), "+f"(d[3]), "+f"(d[4]), "+f"(d[5]), "+f"(d[6]), "+f"(d[7]), "+f"(d[8]), "+f"(d[9]), "+f"(d[10]), "+f"(d[11])
    : "r"(a0), "r"(a1), "r"(a2), "r"(a3), "l"(descB), "r"(scaleD), "n"(TB));
}


__device__ __forceinline__ void ln_prologue(const bf16* __restrict__ src, int row0, uint8_t* sA, int ctid) {
  const int warp = ctid >> 5, lane = ctid & 31;
  for (int rr = 0; rr < 16; rr += 8) {
    uint2 v[8][5];
#pragma unroll
    for (int u = 0; u < 8; u++) {
      const uint2* p = reinterpret_cast<const uint2*>(src + (size_t)(row0 + warp * 16 + rr + u) * DM);
#pragma unroll
      for (int j = 0; j < 5; j++) v[u][j] = p[lane + 32 * j];
    }
#pragma unroll
    for (int u = 0; u < 8; u++) {
      float f[20];
#pragma unroll
      for (int j = 0; j < 5; j++) {
        f[4 * j + 0] = __uint_as_float(v[u][j].x << 16);
        f[4 * j + 1] = __uint_as_float(v[u][j].x & 0xffff0000u);
        f[4 * j + 2] = __uint_as_float(v[u][j].y << 16);
        f[4 * j + 3] = __uint_as_float(v[u][j].y & 0xffff0000u);
      }
      float s = 0.f;
#pragma unroll
      for (int j = 0; j < 20; j++) s += f[j];
#pragma unroll
      for (int o = 16; o > 0; o >>= 1) s += __shfl_xor_sync(0xffffffffu, s, o);
      const float mean = s * (1.0f / DM);
      float q = 0.f;
#pragma unroll
      for (int j = 0; j < 20; j++) { f[j] -= mean; q += f[j] * f[j]; }
#pragma unroll
      for (int o = 16; o > 0; o >>= 1) q += __shfl_xor_sync(0xffffffffu, q, o);
      const float rstd = rsqrtf(q * (1.0f / DM) + 1e-5f);
      const int r = warp * 16 + rr + u;
#pragma unroll
      for (int j = 0; j < 5; j++) {
        const int e = (lane + 32 * j) * 4;
        const int kb = e >> 6;
        const int byte = (e & 63) * 2;
        const int chunk = byte >> 4;
        const int sw = ((chunk ^ (r & 7)) << 4) | (byte & 15);
        uint2 o;
        o.x = pack_bf16(f[4 * j + 0] * rstd, f[4 * j + 1] * rstd);
        o.y = pack_bf16(f[4 * j + 2] * rstd, f[4 * j + 3] * rstd);
        *reinterpret_cast<uint2*>(sA + kb * 16384 + r * 128 + sw) = o;
      }
    }
  }
}

constexpr int K1_STAGES = 4;
constexpr int K1_SMEM = 163840 + K1_STAGES * 16384 + 1024;
__global__ void __launch_bounds__(288, 1) k1_ln_qkv(const bf16* __restrict__ x, const __grid_constant__ CUtensorMap tmW) {
  extern __shared__ __align__(1024) uint8_t smem[];
  uint8_t* sA = smem;
  uint8_t* sB = smem + 163840;
  const uint32_t bar0 = smem_u32(smem + 163840 + K1_STAGES * 16384);
  const int tid = threadIdx.x;
  const int mblk = blockIdx.x >> 3, nblk = blockIdx.x & 7;
  if (tid == 0) {
    for (int s = 0; s < K1_STAGES; s++) { mbar_init(bar0 + 8 * s, 1); mbar_init(bar0 + 64 + 8 * s, 2); }
    asm volatile("fence.mbarrier_init.release.cluster;" ::: "memory");
  }
  __syncthreads();
  if (tid >= 256) {
    if (tid == 256) {
      for (int it = 0; it < 20; it++) {
        const int s = it % K1_STAGES;
        mbar_wait(bar0 + 64 + 8 * s, ((it / K1_STAGES) & 1) ^ 1);
        mbar_expect_tx(bar0 + 8 * s, 16384);
        for (int b = 0; b < 4; b++)
          tma_load_2d(smem_u32(sB + s * 16384 + b * 4096), &tmW, nblk * 240 + b * 64, it * 32, bar0 + 8 * s);
      }
    }
    return;
  }
  ln_prologue(x, mblk * 128, sA, tid);
  fence_async_smem();
  named_bar_sync(1, 256);
  const int wg = tid >> 7;
  float acc[120];
#pragma unroll
  for (int i = 0; i < 120; i++) acc[i] = 0.f;
  const uint32_t aBase = smem_u32(sA) + wg * 64 * 128;
  const uint32_t bBase = smem_u32(sB);
  for (int it = 0; it < 20; it++) {
    const int s = it % K1_STAGES;
    mbar_wait(bar0 + 8 * s, (it / K1_STAGES) & 1);
    wg_fence();
#pragma unroll
    for (int kk = 0; kk < 2; kk++) {
      uint64_t da = make_desc(aBase + (it >> 1) * 16384 + (it & 1) * 64 + kk * 32, 16, 1024, 1);
      uint64_t db = make_desc(bBase + s * 16384 + kk * 2048, 4096, 1024, 1);
      wgmma_ss_n240<1>(acc, da, db, 1);
    }
    wg_commit();
    wg_wait<1>();
    if (it > 0 && (tid & 127) == 0) mbar_arrive(bar0 + 64 + 8 * ((it - 1) % K1_STAGES));
  }
  wg_wait<0>();
  reg_fence(acc);
  named_bar_sync(2 + wg, 128);
  const int lane = tid & 31, q = lane & 3;
  const int r = ((tid & 127) >> 5) * 16 + (lane >> 2);
  uint8_t* stg = sA + wg * 8192;
#pragma unroll
  for (int i = 0; i < 30; i++) {
    const int col = 8 * i + 2 * q;
    const int sl = col / 20, d = col - sl * 20;
    uint8_t* p = stg + (sl >> 1) * 16384 + (sl & 1) * 4096 + r * 64 + d * 2;
    *reinterpret_cast<uint32_t*>(p) = pack_bf16(acc[4 * i], acc[4 * i + 1]);
    *reinterpret_cast<uint32_t*>(p + 512) = pack_bf16(acc[4 * i + 2], acc[4 * i + 3]);
  }
  for (int t = tid & 127; t < 64 * 12 * 3; t += 128) {
    const int part = t % 3, sl = (t / 3) % 12, rr = t / 36;
    uint2 val = make_uint2(0u, 0u);
    if (nblk * 12 + sl >= 64 && part == 0) val.x = 0x00003F80u;
    *reinterpret_cast<uint2*>(stg + (sl >> 1) * 16384 + (sl & 1) * 4096 + rr * 64 + 40 + part * 8) = val;
  }
  fence_async_smem();
  named_bar_sync(2 + wg, 128);
  if ((tid & 127) < 12) {
    const int sl = tid & 127;
    bf16* dst = g_qkv + ((size_t)(nblk * 12 + sl) * SEQ + mblk * 128 + wg * 64) * 32;
    asm volatile("cp.async.bulk.global.shared::cta.bulk_group [%0], [%1], 4096;" :: "l"(dst), "r"(smem_u32(stg + (sl >> 1) * 16384 + (sl & 1) * 4096)) : "memory");
    asm volatile("cp.async.bulk.commit_group;" ::: "memory");
    asm volatile("cp.async.bulk.wait_group.read 0;" ::: "memory");
  }
}

constexpr int K2_STAGES = 6;
constexpr int K2_SMEM = 16384 + K2_STAGES * 16384 + 1024;
__global__ void __launch_bounds__(512, 1) k2_attn(const __grid_constant__ CUtensorMap tmQKV) {
  extern __shared__ __align__(1024) uint8_t smem[];
  uint8_t* sQ = smem;
  uint8_t* sKV = smem + 16384;
  const uint32_t bar0 = smem_u32(smem + 16384 + K2_STAGES * 16384);
  const int tid = threadIdx.x;
  const int head = blockIdx.x >> 3, qblk = blockIdx.x & 7;
  if (tid == 0) {
    for (int s = 0; s < K2_STAGES; s++) { mbar_init(bar0 + 8 * s, 1); mbar_init(bar0 + 64 + 8 * s, 4); }
    mbar_init(bar0 + 128, 1);
    asm volatile("fence.mbarrier_init.release.cluster;" ::: "memory");
  }
  __syncthreads();
  if (tid == 0) {
    mbar_expect_tx(bar0 + 128, 16384);
    tma_load_2d(smem_u32(sQ), &tmQKV, 0, head * SEQ + qblk * 256, bar0 + 128);
    tma_load_2d(smem_u32(sQ) + 8192, &tmQKV, 0, head * SEQ + qblk * 256 + 128, bar0 + 128);
    for (int it = 0; it < K2_STAGES - 1; it++) {
      mbar_expect_tx(bar0 + 8 * it, 16384);
      tma_load_2d(smem_u32(sKV + it * 16384), &tmQKV, 0, (32 + head) * SEQ + it * 128, bar0 + 8 * it);
      tma_load_2d(smem_u32(sKV + it * 16384 + 8192), &tmQKV, 0, (64 + head) * SEQ + it * 128, bar0 + 8 * it);
    }
  }
  const int wg = tid >> 7, lane = tid & 31;
  const float c = 0.22360679774997896f * 1.4426950408889634f;
  float o[12];
#pragma unroll
  for (int i = 0; i < 12; i++) o[i] = 0.f;
  float m0 = -INFINITY, m1 = -INFINITY;
  const uint32_t qBase = smem_u32(sQ) + wg * 4096;
  mbar_wait(bar0 + 128, 0);
  for (int it = 0; it < 16; it++) {
    const int s = it % K2_STAGES;
    const uint32_t kBase = smem_u32(sKV + s * 16384), vBase = kBase + 8192;
    float sc[64];
    if (tid == 0 && it + K2_STAGES - 1 < 16) {
      const int n = it + K2_STAGES - 1, ns = n % K2_STAGES;
      mbar_wait(bar0 + 64 + 8 * ns, ((n / K2_STAGES) & 1) ^ 1);
      mbar_expect_tx(bar0 + 8 * ns, 16384);
      tma_load_2d(smem_u32(sKV + ns * 16384), &tmQKV, 0, (32 + head) * SEQ + n * 128, bar0 + 8 * ns);
      tma_load_2d(smem_u32(sKV + ns * 16384 + 8192), &tmQKV, 0, (64 + head) * SEQ + n * 128, bar0 + 8 * ns);
    }
    __syncwarp();
    mbar_wait(bar0 + 8 * s, (it / K2_STAGES) & 1);
    wg_fence();
#pragma unroll
    for (int kk = 0; kk < 2; kk++)
      wgmma_ss_n128<0>(sc, make_desc(qBase + kk * 32, 16, 512, 2), make_desc(kBase + kk * 32, 16, 512, 2), kk);
    wg_commit();
    wg_wait<0>();
    reg_fence(sc);
    float mx0 = m0, mx1 = m1;
#pragma unroll
    for (int i = 0; i < 16; i++) {
      mx0 = fmaxf(mx0, fmaxf(sc[4 * i], sc[4 * i + 1]));
      mx1 = fmaxf(mx1, fmaxf(sc[4 * i + 2], sc[4 * i + 3]));
    }
    mx0 = fmaxf(mx0, __shfl_xor_sync(0xffffffffu, mx0, 1)); mx0 = fmaxf(mx0, __shfl_xor_sync(0xffffffffu, mx0, 2));
    mx1 = fmaxf(mx1, __shfl_xor_sync(0xffffffffu, mx1, 1)); mx1 = fmaxf(mx1, __shfl_xor_sync(0xffffffffu, mx1, 2));
    const float a0 = ex2((m0 - mx0) * c), a1 = ex2((m1 - mx1) * c);
    m0 = mx0; m1 = mx1;
    const float nb0 = -mx0 * c, nb1 = -mx1 * c;
    uint32_t p[32];
#pragma unroll
    for (int i = 0; i < 16; i++) {
      p[2 * i] = pack_bf16(ex2(fmaf(sc[4 * i], c, nb0)), ex2(fmaf(sc[4 * i + 1], c, nb0)));
      p[2 * i + 1] = pack_bf16(ex2(fmaf(sc[4 * i + 2], c, nb1)), ex2(fmaf(sc[4 * i + 3], c, nb1)));
    }
#pragma unroll
    for (int i = 0; i < 3; i++) { o[4 * i] *= a0; o[4 * i + 1] *= a0; o[4 * i + 2] *= a1; o[4 * i + 3] *= a1; }
    wg_fence();
#pragma unroll
    for (int kk = 0; kk < 8; kk++)
      wgmma_rs_n24<1>(o, p[4 * kk], p[4 * kk + 1], p[4 * kk + 2], p[4 * kk + 3], make_desc(vBase + kk * 1024, 16, 512, 2), 1);
    wg_commit();
    wg_wait<0>();
    reg_fence(o);
    if ((tid & 127) == 0) mbar_arrive(bar0 + 64 + 8 * s);
  }
  const float l0 = __shfl_sync(0xffffffffu, o[8], (lane & ~3) | 2);
  const float l1 = __shfl_sync(0xffffffffu, o[10], (lane & ~3) | 2);
  const float i0 = 1.0f / l0, i1 = 1.0f / l1;
  const int q = lane & 3;
  const int row = qblk * 256 + wg * 64 + ((tid & 127) >> 5) * 16 + (lane >> 2);
#pragma unroll
  for (int i = 0; i < 3; i++) {
    const int d = 8 * i + 2 * q;
    if (d < 20) {
      *reinterpret_cast<uint32_t*>(g_o + (size_t)row * DM + head * 20 + d) = pack_bf16(o[4 * i] * i0, o[4 * i + 1] * i0);
      *reinterpret_cast<uint32_t*>(g_o + (size_t)(row + 8) * DM + head * 20 + d) = pack_bf16(o[4 * i + 2] * i1, o[4 * i + 3] * i1);
    }
  }
}

constexpr int G_STAGES = 6;
constexpr int G_STAGE_BYTES = 16384 + 16384;
constexpr int G_SMEM = G_STAGES * G_STAGE_BYTES + 1024;
template <int KTOT>
__global__ void __launch_bounds__(288, 1) k_gemm_res(const __grid_constant__ CUtensorMap tmA, const __grid_constant__ CUtensorMap tmB,
                                                     const bf16* __restrict__ res, bf16* __restrict__ out) {
  extern __shared__ __align__(1024) uint8_t smem[];
  const uint32_t bar0 = smem_u32(smem + G_STAGES * G_STAGE_BYTES);
  const int tid = threadIdx.x;
  const int mblk = blockIdx.x >> 3, nblk = blockIdx.x & 7;
  constexpr int NIT = KTOT / 64;
  if (tid == 0) {
    for (int s = 0; s < G_STAGES; s++) { mbar_init(bar0 + 8 * s, 1); mbar_init(bar0 + 64 + 8 * s, 2); }
    asm volatile("fence.mbarrier_init.release.cluster;" ::: "memory");
  }
  __syncthreads();
  if (tid >= 256) {
    if (tid == 256) {
      for (int it = 0; it < NIT; it++) {
        const int s = it % G_STAGES;
        mbar_wait(bar0 + 64 + 8 * s, ((it / G_STAGES) & 1) ^ 1);
        mbar_expect_tx(bar0 + 8 * s, G_STAGE_BYTES);
        const uint32_t st = smem_u32(smem + s * G_STAGE_BYTES);
        tma_load_2d(st, &tmA, it * 64, mblk * 128, bar0 + 8 * s);
        tma_load_2d(st + 16384, &tmB, nblk * 80, it * 64, bar0 + 8 * s);
        tma_load_2d(st + 16384 + 8192, &tmB, nblk * 80 + 64, it * 64, bar0 + 8 * s);
      }
    }
    return;
  }
  const int wg = tid >> 7;
  float acc[40];
#pragma unroll
  for (int i = 0; i < 40; i++) acc[i] = 0.f;
  for (int it = 0; it < NIT; it++) {
    const int s = it % G_STAGES;
    const uint32_t st = smem_u32(smem + s * G_STAGE_BYTES);
    mbar_wait(bar0 + 8 * s, (it / G_STAGES) & 1);
    wg_fence();
#pragma unroll
    for (int kk = 0; kk < 4; kk++) {
      uint64_t da = make_desc(st + wg * 8192 + kk * 32, 16, 1024, 1);
      uint64_t db = make_desc(st + 16384 + kk * 2048, 8192, 1024, 1);
      wgmma_ss_n80<1>(acc, da, db, 1);
    }
    wg_commit();
    wg_wait<1>();
    if (it > 0 && (tid & 127) == 0) mbar_arrive(bar0 + 64 + 8 * ((it - 1) % G_STAGES));
  }
  wg_wait<0>();
  reg_fence(acc);
  const int lane = tid & 31, q = lane & 3;
  const int row = mblk * 128 + wg * 64 + ((tid & 127) >> 5) * 16 + (lane >> 2);
#pragma unroll
  for (int i = 0; i < 10; i++) {
    const int col = nblk * 80 + 8 * i + 2 * q;
    const uint32_t r0 = *reinterpret_cast<const uint32_t*>(res + (size_t)row * DM + col);
    const uint32_t r1 = *reinterpret_cast<const uint32_t*>(res + (size_t)(row + 8) * DM + col);
    *reinterpret_cast<uint32_t*>(out + (size_t)row * DM + col) =
        pack_bf16(acc[4 * i] + __uint_as_float(r0 << 16), acc[4 * i + 1] + __uint_as_float(r0 & 0xffff0000u));
    *reinterpret_cast<uint32_t*>(out + (size_t)(row + 8) * DM + col) =
        pack_bf16(acc[4 * i + 2] + __uint_as_float(r1 << 16), acc[4 * i + 3] + __uint_as_float(r1 & 0xffff0000u));
  }
}

constexpr int K4_STAGES = 4;
constexpr int K4_SMEM = 163840 + K4_STAGES * 16384 + 1024;
__global__ void __launch_bounds__(288, 1) k4_ln_ffn(const __grid_constant__ CUtensorMap tmG, const __grid_constant__ CUtensorMap tmU) {
  extern __shared__ __align__(1024) uint8_t smem[];
  uint8_t* sA = smem;
  uint8_t* sB = smem + 163840;
  const uint32_t bar0 = smem_u32(smem + 163840 + K4_STAGES * 16384);
  const int tid = threadIdx.x;
  const int mblk = blockIdx.x >> 3, nblk = blockIdx.x & 7;
  if (tid == 0) {
    for (int s = 0; s < K4_STAGES; s++) { mbar_init(bar0 + 8 * s, 1); mbar_init(bar0 + 64 + 8 * s, 2); }
    asm volatile("fence.mbarrier_init.release.cluster;" ::: "memory");
  }
  __syncthreads();
  if (tid >= 256) {
    if (tid == 256) {
      for (int it = 0; it < 30; it++) {
        const int s = it % K4_STAGES;
        const int pass = it / 10, kb = it % 10;
        mbar_wait(bar0 + 64 + 8 * s, ((it / K4_STAGES) & 1) ^ 1);
        mbar_expect_tx(bar0 + 8 * s, 16384);
        tma_load_2d(smem_u32(sB + s * 16384), &tmG, nblk * 192 + pass * 64, kb * 64, bar0 + 8 * s);
        tma_load_2d(smem_u32(sB + s * 16384 + 8192), &tmU, nblk * 192 + pass * 64, kb * 64, bar0 + 8 * s);
      }
    }
    return;
  }
  ln_prologue(g_h, mblk * 128, sA, tid);
  fence_async_smem();
  named_bar_sync(1, 256);
  const int wg = tid >> 7;
  const uint32_t aBase = smem_u32(sA) + wg * 64 * 128;
  const uint32_t bBase = smem_u32(sB);
  const int lane = tid & 31, q = lane & 3;
  const int row = mblk * 128 + wg * 64 + ((tid & 127) >> 5) * 16 + (lane >> 2);
  for (int pass = 0; pass < 3; pass++) {
    float acc[64];
#pragma unroll
    for (int i = 0; i < 64; i++) acc[i] = 0.f;
    for (int kb = 0; kb < 10; kb++) {
      const int it = pass * 10 + kb;
      const int s = it % K4_STAGES;
      mbar_wait(bar0 + 8 * s, (it / K4_STAGES) & 1);
      wg_fence();
#pragma unroll
      for (int kk = 0; kk < 4; kk++) {
        uint64_t da = make_desc(aBase + kb * 16384 + kk * 32, 16, 1024, 1);
        uint64_t db = make_desc(bBase + s * 16384 + kk * 2048, 8192, 1024, 1);
        wgmma_ss_n128<1>(acc, da, db, 1);
      }
      wg_commit();
      wg_wait<1>();
      if (kb > 0 && (tid & 127) == 0) mbar_arrive(bar0 + 64 + 8 * ((it - 1) % K4_STAGES));
    }
    wg_wait<0>();
    if ((tid & 127) == 0) mbar_arrive(bar0 + 64 + 8 * ((pass * 10 + 9) % K4_STAGES));
    reg_fence(acc);
#pragma unroll
    for (int i = 0; i < 8; i++) {
      const int col = nblk * 192 + pass * 64 + 8 * i + 2 * q;
      float r[4];
#pragma unroll
      for (int j = 0; j < 4; j++) {
        const float g = acc[4 * i + j], u = acc[32 + 4 * i + j];
        r[j] = g / (1.0f + __expf(-g)) * u;
      }
      *reinterpret_cast<uint32_t*>(g_act + (size_t)row * FF + col) = pack_bf16(r[0], r[1]);
      *reinterpret_cast<uint32_t*>(g_act + (size_t)(row + 8) * FF + col) = pack_bf16(r[2], r[3]);
    }
  }
}

typedef CUresult (*EncodeFn)(CUtensorMap*, CUtensorMapDataType, cuuint32_t, void*, const cuuint64_t*, const cuuint64_t*,
                             const cuuint32_t*, const cuuint32_t*, CUtensorMapInterleave, CUtensorMapSwizzle,
                             CUtensorMapL2promotion, CUtensorMapFloatOOBfill);
static void make_map(EncodeFn fn, CUtensorMap* m, const void* ptr, uint64_t cols, uint64_t rows, uint32_t bc, uint32_t br,
                     CUtensorMapSwizzle sw) {
  cuuint64_t dims[2] = {cols, rows};
  cuuint64_t strides[1] = {cols * 2};
  cuuint32_t box[2] = {bc, br};
  cuuint32_t es[2] = {1, 1};
  fn(m, CU_TENSOR_MAP_DATA_TYPE_BFLOAT16, 2, const_cast<void*>(ptr), dims, strides, box, es, CU_TENSOR_MAP_INTERLEAVE_NONE, sw,
     CU_TENSOR_MAP_L2_PROMOTION_L2_128B, CU_TENSOR_MAP_FLOAT_OOB_FILL_NONE);
}

extern "C" void kernel_launch(void* const* d_in, const int* in_sizes, int n_in, void* d_out, int out_size) {
  const bf16* x = (const bf16*)d_in[0];
  const bf16* wqkv = (const bf16*)d_in[1];
  const bf16* wo = (const bf16*)d_in[2];
  const bf16* wg = (const bf16*)d_in[4];
  const bf16* wu = (const bf16*)d_in[5];
  const bf16* wd = (const bf16*)d_in[6];
  bf16* out = (bf16*)d_out;
  static EncodeFn fn = nullptr;
  static void *p_qkv, *p_o, *p_h, *p_act;
  if (!fn) {
    void* f = nullptr;
    cudaDriverEntryPointQueryResult qr;
    cudaGetDriverEntryPoint("cuTensorMapEncodeTiled", &f, cudaEnableDefault, &qr);
    fn = (EncodeFn)f;
    cudaGetSymbolAddress(&p_qkv, g_qkv);
    cudaGetSymbolAddress(&p_o, g_o);
    cudaGetSymbolAddress(&p_h, g_h);
    cudaGetSymbolAddress(&p_act, g_act);
    cudaFuncSetAttribute(k1_ln_qkv, cudaFuncAttributeMaxDynamicSharedMemorySize, K1_SMEM);
    cudaFuncSetAttribute(k2_attn, cudaFuncAttributeMaxDynamicSharedMemorySize, K2_SMEM);
    cudaFuncSetAttribute(k_gemm_res<640>, cudaFuncAttributeMaxDynamicSharedMemorySize, G_SMEM);
    cudaFuncSetAttribute(k_gemm_res<1536>, cudaFuncAttributeMaxDynamicSharedMemorySize, G_SMEM);
    cudaFuncSetAttribute(k4_ln_ffn, cudaFuncAttributeMaxDynamicSharedMemorySize, K4_SMEM);
  }
  CUtensorMap mWqkv, mQKV, mO, mWo, mWg, mWu, mAct, mWd;
  make_map(fn, &mWqkv, wqkv, 3 * DM, DM, 64, 32, CU_TENSOR_MAP_SWIZZLE_128B);
  make_map(fn, &mQKV, p_qkv, 32, 3 * NH * SEQ, 32, 128, CU_TENSOR_MAP_SWIZZLE_64B);
  make_map(fn, &mO, p_o, DM, SEQ, 64, 128, CU_TENSOR_MAP_SWIZZLE_128B);
  make_map(fn, &mWo, wo, DM, DM, 64, 64, CU_TENSOR_MAP_SWIZZLE_128B);
  make_map(fn, &mWg, wg, FF, DM, 64, 64, CU_TENSOR_MAP_SWIZZLE_128B);
  make_map(fn, &mWu, wu, FF, DM, 64, 64, CU_TENSOR_MAP_SWIZZLE_128B);
  make_map(fn, &mAct, p_act, FF, SEQ, 64, 128, CU_TENSOR_MAP_SWIZZLE_128B);
  make_map(fn, &mWd, wd, DM, FF, 64, 64, CU_TENSOR_MAP_SWIZZLE_128B);
  k1_ln_qkv<<<128, 288, K1_SMEM>>>(x, mWqkv);
  k2_attn<<<256, 512, K2_SMEM>>>(mQKV);
  k_gemm_res<640><<<128, 288, G_SMEM>>>(mO, mWo, x, (bf16*)p_h);
  k4_ln_ffn<<<128, 288, K4_SMEM>>>(mWg, mWu);
  k_gemm_res<1536><<<128, 288, G_SMEM>>>(mAct, mWd, (const bf16*)p_h, out);
}
```

```cpp
#include <cuda_runtime.h>
#include <cuda_bf16.h>
#include <cuda.h>
#include <stdint.h>

typedef __nv_bfloat16 bf16;

constexpr int SEQ = 2048, DM = 640, NH = 32, DH = 20, FF = 1536;

__device__ __align__(1024) bf16 g_qkv[3 * NH * SEQ * 32];
__device__ __align__(1024) bf16 g_o[SEQ * DM];
__device__ __align__(1024) bf16 g_h[SEQ * DM];
__device__ __align__(1024) bf16 g_act[SEQ * FF];

__device__ __forceinline__ uint32_t smem_u32(const void* p) { return (uint32_t)__cvta_generic_to_shared(p); }
__device__ __forceinline__ void mbar_init(uint32_t bar, uint32_t count) {
  asm volatile("mbarrier.init.shared::cta.b64 [%0], %1;" :: "r"(bar), "r"(count) : "memory");
}
__device__ __forceinline__ void mbar_expect_tx(uint32_t bar, uint32_t bytes) {
  asm volatile("mbarrier.arrive.expect_tx.shared::cta.b64 _, [%0], %1;" :: "r"(bar), "r"(bytes) : "memory");
}
__device__ __forceinline__ void mbar_arrive(uint32_t bar) {
  asm volatile("mbarrier.arrive.shared::cta.b64 _, [%0];" :: "r"(bar) : "memory");
}
__device__ __forceinline__ void mbar_wait(uint32_t bar, uint32_t parity) {
  uint32_t done;
  uint32_t it = 0;
  do {
    asm volatile("{\n.reg .pred p;\nmbarrier.try_wait.parity.shared::cta.b64 p, [%1], %2;\nselp.u32 %0, 1, 0, p;\n}"
                 : "=r"(done) : "r"(bar), "r"(parity) : "memory");
    if (++it > 4000000u) __trap();
  } while (!done);
}
__device__ __forceinline__ void tma_load_2d(uint32_t dst, const CUtensorMap* map, int c0, int c1, uint32_t bar) {
  asm volatile("cp.async.bulk.tensor.2d.shared::cluster.global.mbarrier::complete_tx::bytes [%0], [%1, {%3, %4}], [%2];"
               :: "r"(dst), "l"((uint64_t)map), "r"(bar), "r"(c0), "r"(c1) : "memory");
}
__device__ __forceinline__ void fence_async_smem() { asm volatile("fence.proxy.async.shared::cta;" ::: "memory"); }
__device__ __forceinline__ void wg_fence() { asm volatile("wgmma.fence.sync.aligned;" ::: "memory"); }
__device__ __forceinline__ void wg_commit() { asm volatile("wgmma.commit_group.sync.aligned;" ::: "memory"); }
template <int N> __device__ __forceinline__ void wg_wait() { asm volatile("wgmma.wait_group.sync.aligned %0;" :: "n"(N) : "memory"); }
template <int N> __device__ __forceinline__ void reg_fence(float (&d)[N]) {
#pragma unroll
  for (int i = 0; i < N; i++) asm volatile("" : "+f"(d[i]) :: "memory");
}
__device__ __forceinline__ uint64_t make_desc(uint32_t addr, uint32_t lbo, uint32_t sbo, uint32_t swz) {
  return (uint64_t)((addr & 0x3FFFF) >> 4) | ((uint64_t)(lbo >> 4) << 16) | ((uint64_t)(sbo >> 4) << 32) | ((uint64_t)swz << 62);
}
__device__ __forceinline__ uint32_t pack_bf16(float a, float b) {
  __nv_bfloat162 v = __floats2bfloat162_rn(a, b);
  return *reinterpret_cast<uint32_t*>(&v);
}
__device__ __forceinline__ float ex2(float x) { float y; asm("ex2.approx.ftz.f32 %0, %1;" : "=f"(y) : "f"(x)); return y; }
__device__ __forceinline__ void named_bar_sync(int id, int n) { asm volatile("bar.sync %0, %1;" :: "r"(id), "r"(n) : "memory"); }

template<int TB> __device__ __forceinline__ void wgmma_ss_n240(float (&d)[120], uint64_t descA, uint64_t descB, int scaleD) {
  asm volatile("{\n.reg .pred p;\nsetp.ne.b32 p, %122, 0;\n"
    "wgmma.mma_async.sync.aligned.m64n240k16.f32.bf16.bf16 {%0, %1, %2, %3, %4, %5, %6, %7, %8, %9, %10, %11, %12, %13, %14, %15, %16, %17, %18, %19, %20, %21, %22, %23, %24, %25, %26, %27, %28, %29, %30, %31, %32, %33, %34, %35, %36, %37, %38, %39, %40, %41, %42, %43, %44, %45, %46, %47, %48, %49, %50, %51, %52, %53, %54, %55, %56, %57, %58, %59, %60, %61, %62, %63, %64, %65, %66, %67, %68, %69, %70, %71, %72, %73, %74, %75, %76, %77, %78, %79, %80, %81, %82, %83, %84, %85, %86, %87, %88, %89, %90, %91, %92, %93, %94, %95, %96, %97, %98, %99, %100, %101, %102, %103, %104, %105, %106, %107, %108, %109, %110, %111, %112, %113, %114, %115, %116, %117, %118, %119}, %120, %121, p, 1, 1, 0, %123;\n}"
    : "+f"(d[0]), "+f"(d[1]), "+f"(d[2]), "+f"(d[3]), "+f"(d[4]), "+f"(d[5]), "+f"(d[6]), "+f"(d[7]), "+f"(d[8]), "+f"(d[9]), "+f"(d[10]), "+f"(d[11]), "+f"(d[12]), "+f"(d[13]), "+f"(d[14]), "+f"(d[15]), "+f"(d[16]), "+f"(d[17]), "+f"(d[18]), "+f"(d[19]), "+f"(d[20]), "+f"(d[21]), "+f"(d[22]), "+f"(d[23]), "+f"(d[24]), "+f"(d[25]), "+f"(d[26]), "+f"(d[27]), "+f"(d[28]), "+f"(d[29]), "+f"(d[30]), "+f"(d[31]), "+f"(d[32]), "+f"(d[33]), "+f"(d[34]), "+f"(d[35]), "+f"(d[36]), "+f"(d[37]), "+f"(d[38]), "+f"(d[39]), "+f"(d[40]), "+f"(d[41]), "+f"(d[42]), "+f"(d[43]), "+f"(d[44]), "+f"(d[45]), "+f"(d[46]), "+f"(d[47]), "+f"(d[48]), "+f"(d[49]), "+f"(d[50]), "+f"(d[51]), "+f"(d[52]), "+f"(d[53]), "+f"(d[54]), "+f"(d[55]), "+f"(d[56]), "+f"(d[57]), "+f"(d[58]), "+f"(d[59]), "+f"(d[60]), "+f"(d[61]), "+f"(d[62]), "+f"(d[63]), "+f"(d[64]), "+f"(d[65]), "+f"(d[66]), "+f"(d[67]), "+f"(d[68]), "+f"(d[69]), "+f"(d[70]), "+f"(d[71]), "+f"(d[72]), "+f"(d[73]), "+f"(d[74]), "+f"(d[75]), "+f"(d[76]), "+f"(d[77]), "+f"(d[78]), "+f"(d[79]), "+f"(d[80]), "+f"(d[81]), "+f"(d[82]), "+f"(d[83]), "+f"(d[84]), "+f"(d[85]), "+f"(d[86]), "+f"(d[87]), "+f"(d[88]), "+f"(d[89]), "+f"(d[90]), "+f"(d[91]), "+f"(d[92]), "+f"(d[93]), "+f"(d[94]), "+f"(d[95]), "+f"(d[96]), "+f"(d[97]), "+f"(d[98]), "+f"(d[99]), "+f"(d[100]), "+f"(d[101]), "+f"(d[102]), "+f"(d[103]), "+f"(d[104]), "+f"(d[105]), "+f"(d[106]), "+f"(d[107]), "+f"(d[108]), "+f"(d[109]), "+f"(d[110]), "+f"(d[111]), "+f"(d[112]), "+f"(d[113]), "+f"(d[114]), "+f"(d[115]), "+f"(d[116]), "+f"(d[117]), "+f"(d[118]), "+f"(d[119])
    : "l"(descA), "l"(descB), "r"(scaleD), "n"(TB));
}
template<int TB> __device__ __forceinline__ void wgmma_ss_n128(float (&d)[64], uint64_t descA, uint64_t descB, int scaleD) {
  asm volatile("{\n.reg .pred p;\nsetp.ne.b32 p, %66, 0;\n"
    "wgmma.mma_async.sync.aligned.m64n128k16.f32.bf16.bf16 {%0, %1, %2, %3, %4, %5, %6, %7, %8, %9, %10, %11, %12, %13, %14, %15, %16, %17, %18, %19, %20, %21, %22, %23, %24, %25, %26, %27, %28, %29, %30, %31, %32, %33, %34, %35, %36, %37, %38, %39, %40, %41, %42, %43, %44, %45, %46, %47, %48, %49, %50, %51, %52, %53, %54, %55, %56, %57, %58, %59, %60, %61, %62, %63}, %64, %65, p, 1, 1, 0, %67;\n}"
    : "+f"(d[0]), "+f"(d[1]), "+f"(d[2]), "+f"(d[3]), "+f"(d[4]), "+f"(d[5]), "+f"(d[6]), "+f"(d[7]), "+f"(d[8]), "+f"(d[9]), "+f"(d[10]), "+f"(d[11]), "+f"(d[12]), "+f"(d[13]), "+f"(d[14]), "+f"(d[15]), "+f"(d[16]), "+f"(d[17]), "+f"(d[18]), "+f"(d[19]), "+f"(d[20]), "+f"(d[21]), "+f"(d[22]), "+f"(d[23]), "+f"(d[24]), "+f"(d[25]), "+f"(d[26]), "+f"(d[27]), "+f"(d[28]), "+f"(d[29]), "+f"(d[30]), "+f"(d[31]), "+f"(d[32]), "+f"(d[33]), "+f"(d[34]), "+f"(d[35]), "+f"(d[36]), "+f"(d[37]), "+f"(d[38]), "+f"(d[39]), "+f"(d[40]), "+f"(d[41]), "+f"(d[42]), "+f"(d[43]), "+f"(d[44]), "+f"(d[45]), "+f"(d[46]), "+f"(d[47]), "+f"(d[48]), "+f"(d[49]), "+f"(d[50]), "+f"(d[51]), "+f"(d[52]), "+f"(d[53]), "+f"(d[54]), "+f"(d[55]), "+f"(d[56]), "+f"(d[57]), "+f"(d[58]), "+f"(d[59]), "+f"(d[60]), "+f"(d[61]), "+f"(d[62]), "+f"(d[63])
    : "l"(descA), "l"(descB), "r"(scaleD), "n"(TB));
}
template<int TB> __device__ __forceinline__ void wgmma_ss_n80(float (&d)[40], uint64_t descA, uint64_t descB, int scaleD) {
  asm volatile("{\n.reg .pred p;\nsetp.ne.b32 p, %42, 0;\n"
    "wgmma.mma_async.sync.aligned.m64n80k16.f32.bf16.bf16 {%0, %1, %2, %3, %4, %5, %6, %7, %8, %9, %10, %11, %12, %13, %14, %15, %16, %17, %18, %19, %20, %21, %22, %23, %24, %25, %26, %27, %28, %29, %30, %31, %32, %33, %34, %35, %36, %37, %38, %39}, %40, %41, p, 1, 1, 0, %43;\n}"
    : "+f"(d[0]), "+f"(d[1]), "+f"(d[2]), "+f"(d[3]), "+f"(d[4]), "+f"(d[5]), "+f"(d[6]), "+f"(d[7]), "+f"(d[8]), "+f"(d[9]), "+f"(d[10]), "+f"(d[11]), "+f"(d[12]), "+f"(d[13]), "+f"(d[14]), "+f"(d[15]), "+f"(d[16]), "+f"(d[17]), "+f"(d[18]), "+f"(d[19]), "+f"(d[20]), "+f"(d[21]), "+f"(d[22]), "+f"(d[23]), "+f"(d[24]), "+f"(d[25]), "+f"(d[26]), "+f"(d[27]), "+f"(d[28]), "+f"(d[29]), "+f"(d[30]), "+f"(d[31]), "+f"(d[32]), "+f"(d[33]), "+f"(d[34]), "+f"(d[35]), "+f"(d[36]), "+f"(d[37]), "+f"(d[38]), "+f"(d[39])
    : "l"(descA), "l"(descB), "r"(scaleD), "n"(TB));
}
template<int TB> __device__ __forceinline__ void wgmma_rs_n24(float (&d)[12], uint32_t a0, uint32_t a1, uint32_t a2, uint32_t a3, uint64_t descB, int scaleD) {
  asm volatile("{\n.reg .pred p;\nsetp.ne.b32 p, %17, 0;\n"
    "wgmma.mma_async.sync.aligned.m64n24k16.f32.bf16.bf16 {%0, %1, %2, %3, %4, %5, %6, %7, %8, %9, %10, %11}, {%12, %13, %14, %15}, %16, p, 1, 1, %18;\n}"
    : "+f"(d[0]), "+f"(d[1]), "+f"(d[2]), "+f"(d[3]), "+f"(d[4]), "+f"(d[5]), "+f"(d[6]), "+f"(d[7]), "+f"(d[8]), "+f"(d[9]), "+f"(d[10]), "+f"(d[11])
    : "r"(a0), "r"(a1), "r"(a2), "r"(a3), "l"(descB), "r"(scaleD), "n"(TB));
}


__device__ __forceinline__ void ln_prologue(const bf16* __restrict__ src, int row0, uint8_t* sA, int ctid) {
  const int warp = ctid >> 5, lane = ctid & 31;
  for (int rr = 0; rr < 16; rr += 8) {
    uint2 v[8][5];
#pragma unroll
    for (int u = 0; u < 8; u++) {
      const uint2* p = reinterpret_cast<const uint2*>(src + (size_t)(row0 + warp * 16 + rr + u) * DM);
#pragma unroll
      for (int j = 0; j < 5; j++) v[u][j] = p[lane + 32 * j];
    }
#pragma unroll
    for (int u = 0; u < 8; u++) {
      float f[20];
#pragma unroll
      for (int j = 0; j < 5; j++) {
        f[4 * j + 0] = __uint_as_float(v[u][j].x << 16);
        f[4 * j + 1] = __uint_as_float(v[u][j].x & 0xffff0000u);
        f[4 * j + 2] = __uint_as_float(v[u][j].y << 16);
        f[4 * j + 3] = __uint_as_float(v[u][j].y & 0xffff0000u);
      }
      float s = 0.f;
#pragma unroll
      for (int j = 0; j < 20; j++) s += f[j];
#pragma unroll
      for (int o = 16; o > 0; o >>= 1) s += __shfl_xor_sync(0xffffffffu, s, o);
      const float mean = s * (1.0f / DM);
      float q = 0.f;
#pragma unroll
      for (int j = 0; j < 20; j++) { f[j] -= mean; q += f[j] * f[j]; }
#pragma unroll
      for (int o = 16; o > 0; o >>= 1) q += __shfl_xor_sync(0xffffffffu, q, o);
      const float rstd = rsqrtf(q * (1.0f / DM) + 1e-5f);
      const int r = warp * 16 + rr + u;
#pragma unroll
      for (int j = 0; j < 5; j++) {
        const int e = (lane + 32 * j) * 4;
        const int kb = e >> 6;
        const int byte = (e & 63) * 2;
        const int chunk = byte >> 4;
        const int sw = ((chunk ^ (r & 7)) << 4) | (byte & 15);
        uint2 o;
        o.x = pack_bf16(f[4 * j + 0] * rstd, f[4 * j + 1] * rstd);
        o.y = pack_bf16(f[4 * j + 2] * rstd, f[4 * j + 3] * rstd);
        *reinterpret_cast<uint2*>(sA + kb * 16384 + r * 128 + sw) = o;
      }
    }
  }
}

constexpr int K1_STAGES = 4;
constexpr int K1_SMEM = 163840 + K1_STAGES * 16384 + 1024;
__global__ void __launch_bounds__(288, 1) k1_ln_qkv(const bf16* __restrict__ x, const __grid_constant__ CUtensorMap tmW) {
  extern __shared__ __align__(1024) uint8_t smem[];
  uint8_t* sA = smem;
  uint8_t* sB = smem + 163840;
  const uint32_t bar0 = smem_u32(smem + 163840 + K1_STAGES * 16384);
  const int tid = threadIdx.x;
  const int mblk = blockIdx.x >> 3, nblk = blockIdx.x & 7;
  if (tid == 0) {
    for (int s = 0; s < K1_STAGES; s++) { mbar_init(bar0 + 8 * s, 1); mbar_init(bar0 + 64 + 8 * s, 2); }
    asm volatile("fence.mbarrier_init.release.cluster;" ::: "memory");
  }
  __syncthreads();
  if (tid >= 256) {
    if (tid == 256) {
      for (int it = 0; it < 20; it++) {
        const int s = it % K1_STAGES;
        mbar_wait(bar0 + 64 + 8 * s, ((it / K1_STAGES) & 1) ^ 1);
        mbar_expect_tx(bar0 + 8 * s, 16384);
        for (int b = 0; b < 4; b++)
          tma_load_2d(smem_u32(sB + s * 16384 + b * 4096), &tmW, nblk * 240 + b * 64, it * 32, bar0 + 8 * s);
      }
    }
    return;
  }
  ln_prologue(x, mblk * 128, sA, tid);
  fence_async_smem();
  named_bar_sync(1, 256);
  const int wg = tid >> 7;
  float acc[120];
#pragma unroll
  for (int i = 0; i < 120; i++) acc[i] = 0.f;
  const uint32_t aBase = smem_u32(sA) + wg * 64 * 128;
  const uint32_t bBase = smem_u32(sB);
  for (int it = 0; it < 20; it++) {
    const int s = it % K1_STAGES;
    mbar_wait(bar0 + 8 * s, (it / K1_STAGES) & 1);
    wg_fence();
#pragma unroll
    for (int kk = 0; kk < 2; kk++) {
      uint64_t da = make_desc(aBase + (it >> 1) * 16384 + (it & 1) * 64 + kk * 32, 16, 1024, 1);
      uint64_t db = make_desc(bBase + s * 16384 + kk * 2048, 4096, 1024, 1);
      wgmma_ss_n240<1>(acc, da, db, 1);
    }
    wg_commit();
    wg_wait<1>();
    if (it > 0 && (tid & 127) == 0) mbar_arrive(bar0 + 64 + 8 * ((it - 1) % K1_STAGES));
  }
  wg_wait<0>();
  reg_fence(acc);
  named_bar_sync(2 + wg, 128);
  const int lane = tid & 31, q = lane & 3;
  const int r = ((tid & 127) >> 5) * 16 + (lane >> 2);
  uint8_t* stg = sA + wg * 8192;
#pragma unroll
  for (int i = 0; i < 30; i++) {
    const int col = 8 * i + 2 * q;
    const int sl = col / 20, d = col - sl * 20;
    uint8_t* p = stg + (sl >> 1) * 16384 + (sl & 1) * 4096 + r * 64 + d * 2;
    *reinterpret_cast<uint32_t*>(p) = pack_bf16(acc[4 * i], acc[4 * i + 1]);
    *reinterpret_cast<uint32_t*>(p + 512) = pack_bf16(acc[4 * i + 2], acc[4 * i + 3]);
  }
  for (int t = tid & 127; t < 64 * 12 * 3; t += 128) {
    const int part = t % 3, sl = (t / 3) % 12, rr = t / 36;
    uint2 val = make_uint2(0u, 0u);
    if (nblk * 12 + sl >= 64 && part == 0) val.x = 0x00003F80u;
    *reinterpret_cast<uint2*>(stg + (sl >> 1) * 16384 + (sl & 1) * 4096 + rr * 64 + 40 + part * 8) = val;
  }
  fence_async_smem();
  named_bar_sync(2 + wg, 128);
  if ((tid & 127) < 12) {
    const int sl = tid & 127;
    bf16* dst = g_qkv + ((size_t)(nblk * 12 + sl) * SEQ + mblk * 128 + wg * 64) * 32;
    asm volatile("cp.async.bulk.global.shared::cta.bulk_group [%0], [%1], 4096;" :: "l"(dst), "r"(smem_u32(stg + (sl >> 1) * 16384 + (sl & 1) * 4096)) : "memory");
    asm volatile("cp.async.bulk.commit_group;" ::: "memory");
    asm volatile("cp.async.bulk.wait_group.read 0;" ::: "memory");
  }
}

constexpr int K2_STAGES = 6;
constexpr int K2_SMEM = 16384 + K2_STAGES * 16384 + 1024;
__global__ void __launch_bounds__(512, 1) k2_attn(const __grid_constant__ CUtensorMap tmQKV) {
  extern __shared__ __align__(1024) uint8_t smem[];
  uint8_t* sQ = smem;
  uint8_t* sKV = smem + 16384;
  const uint32_t bar0 = smem_u32(smem + 16384 + K2_STAGES * 16384);
  const int tid = threadIdx.x;
  const int head = blockIdx.x >> 3, qblk = blockIdx.x & 7;
  if (tid == 0) {
    for (int s = 0; s < K2_STAGES; s++) { mbar_init(bar0 + 8 * s, 1); mbar_init(bar0 + 64 + 8 * s, 4); }
    mbar_init(bar0 + 128, 1);
    asm volatile("fence.mbarrier_init.release.cluster;" ::: "memory");
  }
  __syncthreads();
  if (tid == 0) {
    mbar_expect_tx(bar0 + 128, 16384);
    tma_load_2d(smem_u32(sQ), &tmQKV, 0, head * SEQ + qblk * 256, bar0 + 128);
    tma_load_2d(smem_u32(sQ) + 8192, &tmQKV, 0, head * SEQ + qblk * 256 + 128, bar0 + 128);
    for (int it = 0; it < K2_STAGES - 2; it++) {
      mbar_expect_tx(bar0 + 8 * it, 16384);
      tma_load_2d(smem_u32(sKV + it * 16384), &tmQKV, 0, (32 + head) * SEQ + it * 128, bar0 + 8 * it);
      tma_load_2d(smem_u32(sKV + it * 16384 + 8192), &tmQKV, 0, (64 + head) * SEQ + it * 128, bar0 + 8 * it);
    }
  }
  const int wg = tid >> 7, lane = tid & 31;
  const float c = 0.22360679774997896f * 1.4426950408889634f;
  float o[12];
#pragma unroll
  for (int i = 0; i < 12; i++) o[i] = 0.f;
  float m0 = -INFINITY, m1 = -INFINITY;
  const uint32_t qBase = smem_u32(sQ) + wg * 4096;
  mbar_wait(bar0 + 128, 0);
  for (int it = 0; it < 16; it++) {
    const int s = it % K2_STAGES;
    const uint32_t kBase = smem_u32(sKV + s * 16384), vBase = kBase + 8192;
    float sc[64];
    if (tid == 0 && it + K2_STAGES - 2 < 16) {
      const int n = it + K2_STAGES - 2, ns = n % K2_STAGES;
      mbar_wait(bar0 + 64 + 8 * ns, ((n / K2_STAGES) & 1) ^ 1);
      mbar_expect_tx(bar0 + 8 * ns, 16384);
      tma_load_2d(smem_u32(sKV + ns * 16384), &tmQKV, 0, (32 + head) * SEQ + n * 128, bar0 + 8 * ns);
      tma_load_2d(smem_u32(sKV + ns * 16384 + 8192), &tmQKV, 0, (64 + head) * SEQ + n * 128, bar0 + 8 * ns);
    }
    __syncwarp();
    mbar_wait(bar0 + 8 * s, (it / K2_STAGES) & 1);
    wg_fence();
#pragma unroll
    for (int kk = 0; kk < 2; kk++)
      wgmma_ss_n128<0>(sc, make_desc(qBase + kk * 32, 16, 512, 2), make_desc(kBase + kk * 32, 16, 512, 2), kk);
    wg_commit();
    wg_wait<0>();
    reg_fence(sc); reg_fence(o);
    if (it > 0 && (tid & 127) == 0) mbar_arrive(bar0 + 64 + 8 * ((it - 1) % K2_STAGES));
    float mx0 = m0, mx1 = m1;
#pragma unroll
    for (int i = 0; i < 16; i++) {
      mx0 = fmaxf(mx0, fmaxf(sc[4 * i], sc[4 * i + 1]));
      mx1 = fmaxf(mx1, fmaxf(sc[4 * i + 2], sc[4 * i + 3]));
    }
    mx0 = fmaxf(mx0, __shfl_xor_sync(0xffffffffu, mx0, 1)); mx0 = fmaxf(mx0, __shfl_xor_sync(0xffffffffu, mx0, 2));
    mx1 = fmaxf(mx1, __shfl_xor_sync(0xffffffffu, mx1, 1)); mx1 = fmaxf(mx1, __shfl_xor_sync(0xffffffffu, mx1, 2));
    const float a0 = ex2((m0 - mx0) * c), a1 = ex2((m1 - mx1) * c);
    m0 = mx0; m1 = mx1;
    const float nb0 = -mx0 * c, nb1 = -mx1 * c;
    uint32_t p[32];
#pragma unroll
    for (int i = 0; i < 16; i++) {
      p[2 * i] = pack_bf16(ex2(fmaf(sc[4 * i], c, nb0)), ex2(fmaf(sc[4 * i + 1], c, nb0)));
      p[2 * i + 1] = pack_bf16(ex2(fmaf(sc[4 * i + 2], c, nb1)), ex2(fmaf(sc[4 * i + 3], c, nb1)));
    }
#pragma unroll
    for (int i = 0; i < 3; i++) { o[4 * i] *= a0; o[4 * i + 1] *= a0; o[4 * i + 2] *= a1; o[4 * i + 3] *= a1; }
    wg_fence();
#pragma unroll
    for (int kk = 0; kk < 8; kk++)
      wgmma_rs_n24<1>(o, p[4 * kk], p[4 * kk + 1], p[4 * kk + 2], p[4 * kk + 3], make_desc(vBase + kk * 1024, 16, 512, 2), 1);
    wg_commit();
  }
  wg_wait<0>();
  reg_fence(o);
  const float l0 = __shfl_sync(0xffffffffu, o[8], (lane & ~3) | 2);
  const float l1 = __shfl_sync(0xffffffffu, o[10], (lane & ~3) | 2);
  const float i0 = 1.0f / l0, i1 = 1.0f / l1;
  const int q = lane & 3;
  const int row = qblk * 256 + wg * 64 + ((tid & 127) >> 5) * 16 + (lane >> 2);
#pragma unroll
  for (int i = 0; i < 3; i++) {
    const int d = 8 * i + 2 * q;
    if (d < 20) {
      *reinterpret_cast<uint32_t*>(g_o + (size_t)row * DM + head * 20 + d) = pack_bf16(o[4 * i] * i0, o[4 * i + 1] * i0);
      *reinterpret_cast<uint32_t*>(g_o + (size_t)(row + 8) * DM + head * 20 + d) = pack_bf16(o[4 * i + 2] * i1, o[4 * i + 3] * i1);
    }
  }
}

constexpr int G_STAGES = 6;
constexpr int G_STAGE_BYTES = 16384 + 16384;
constexpr int G_SMEM = G_STAGES * G_STAGE_BYTES + 1024;
template <int KTOT>
__global__ void __launch_bounds__(288, 1) k_gemm_res(const __grid_constant__ CUtensorMap tmA, const __grid_constant__ CUtensorMap tmB,
                                                     const bf16* __restrict__ res, bf16* __restrict__ out) {
  extern __shared__ __align__(1024) uint8_t smem[];
  const uint32_t bar0 = smem_u32(smem + G_STAGES * G_STAGE_BYTES);
  const int tid = threadIdx.x;
  const int mblk = blockIdx.x >> 3, nblk = blockIdx.x & 7;
  constexpr int NIT = KTOT / 64;
  if (tid == 0) {
    for (int s = 0; s < G_STAGES; s++) { mbar_init(bar0 + 8 * s, 1); mbar_init(bar0 + 64 + 8 * s, 2); }
    asm volatile("fence.mbarrier_init.release.cluster;" ::: "memory");
  }
  __syncthreads();
  if (tid >= 256) {
    if (tid == 256) {
      for (int it = 0; it < NIT; it++) {
        const int s = it % G_STAGES;
        mbar_wait(bar0 + 64 + 8 * s, ((it / G_STAGES) & 1) ^ 1);
        mbar_expect_tx(bar0 + 8 * s, G_STAGE_BYTES);
        const uint32_t st = smem_u32(smem + s * G_STAGE_BYTES);
        tma_load_2d(st, &tmA, it * 64, mblk * 128, bar0 + 8 * s);
        tma_load_2d(st + 16384, &tmB, nblk * 80, it * 64, bar0 + 8 * s);
        tma_load_2d(st + 16384 + 8192, &tmB, nblk * 80 + 64, it * 64, bar0 + 8 * s);
      }
    }
    return;
  }
  const int wg = tid >> 7;
  float acc[40];
#pragma unroll
  for (int i = 0; i < 40; i++) acc[i] = 0.f;
  for (int it = 0; it < NIT; it++) {
    const int s = it % G_STAGES;
    const uint32_t st = smem_u32(smem + s * G_STAGE_BYTES);
    mbar_wait(bar0 + 8 * s, (it / G_STAGES) & 1);
    wg_fence();
#pragma unroll
    for (int kk = 0; kk < 4; kk++) {
      uint64_t da = make_desc(st + wg * 8192 + kk * 32, 16, 1024, 1);
      uint64_t db = make_desc(st + 16384 + kk * 2048, 8192, 1024, 1);
      wgmma_ss_n80<1>(acc, da, db, 1);
    }
    wg_commit();
    wg_wait<1>();
    if (it > 0 && (tid & 127) == 0) mbar_arrive(bar0 + 64 + 8 * ((it - 1) % G_STAGES));
  }
  wg_wait<0>();
  reg_fence(acc);
  const int lane = tid & 31, q = lane & 3;
  const int row = mblk * 128 + wg * 64 + ((tid & 127) >> 5) * 16 + (lane >> 2);
#pragma unroll
  for (int i = 0; i < 10; i++) {
    const int col = nblk * 80 + 8 * i + 2 * q;
    const uint32_t r0 = *reinterpret_cast<const uint32_t*>(res + (size_t)row * DM + col);
    const uint32_t r1 = *reinterpret_cast<const uint32_t*>(res + (size_t)(row + 8) * DM + col);
    *reinterpret_cast<uint32_t*>(out + (size_t)row * DM + col) =
        pack_bf16(acc[4 * i] + __uint_as_float(r0 << 16), acc[4 * i + 1] + __uint_as_float(r0 & 0xffff0000u));
    *reinterpret_cast<uint32_t*>(out + (size_t)(row + 8) * DM + col) =
        pack_bf16(acc[4 * i + 2] + __uint_as_float(r1 << 16), acc[4 * i + 3] + __uint_as_float(r1 & 0xffff0000u));
  }
}

constexpr int K4_STAGES = 4;
constexpr int K4_SMEM = 163840 + K4_STAGES * 16384 + 1024;
__global__ void __launch_bounds__(288, 1) k4_ln_ffn(const __grid_constant__ CUtensorMap tmG, const __grid_constant__ CUtensorMap tmU) {
  extern __shared__ __align__(1024) uint8_t smem[];
  uint8_t* sA = smem;
  uint8_t* sB = smem + 163840;
  const uint32_t bar0 = smem_u32(smem + 163840 + K4_STAGES * 16384);
  const int tid = threadIdx.x;
  const int mblk = blockIdx.x >> 3, nblk = blockIdx.x & 7;
  if (tid == 0) {
    for (int s = 0; s < K4_STAGES; s++) { mbar_init(bar0 + 8 * s, 1); mbar_init(bar0 + 64 + 8 * s, 2); }
    asm volatile("fence.mbarrier_init.release.cluster;" ::: "memory");
  }
  __syncthreads();
  if (tid >= 256) {
    if (tid == 256) {
      for (int it = 0; it < 30; it++) {
        const int s = it % K4_STAGES;
        const int pass = it / 10, kb = it % 10;
        mbar_wait(bar0 + 64 + 8 * s, ((it / K4_STAGES) & 1) ^ 1);
        mbar_expect_tx(bar0 + 8 * s, 16384);
        tma_load_2d(smem_u32(sB + s * 16384), &tmG, nblk * 192 + pass * 64, kb * 64, bar0 + 8 * s);
        tma_load_2d(smem_u32(sB + s * 16384 + 8192), &tmU, nblk * 192 + pass * 64, kb * 64, bar0 + 8 * s);
      }
    }
    return;
  }
  ln_prologue(g_h, mblk * 128, sA, tid);
  fence_async_smem();
  named_bar_sync(1, 256);
  const int wg = tid >> 7;
  const uint32_t aBase = smem_u32(sA) + wg * 64 * 128;
  const uint32_t bBase = smem_u32(sB);
  const int lane = tid & 31, q = lane & 3;
  const int row = mblk * 128 + wg * 64 + ((tid & 127) >> 5) * 16 + (lane >> 2);
  for (int pass = 0; pass < 3; pass++) {
    float acc[64];
#pragma unroll
    for (int i = 0; i < 64; i++) acc[i] = 0.f;
    for (int kb = 0; kb < 10; kb++) {
      const int it = pass * 10 + kb;
      const int s = it % K4_STAGES;
      mbar_wait(bar0 + 8 * s, (it / K4_STAGES) & 1);
      wg_fence();
#pragma unroll
      for (int kk = 0; kk < 4; kk++) {
        uint64_t da = make_desc(aBase + kb * 16384 + kk * 32, 16, 1024, 1);
        uint64_t db = make_desc(bBase + s * 16384 + kk * 2048, 8192, 1024, 1);
        wgmma_ss_n128<1>(acc, da, db, 1);
      }
      wg_commit();
      wg_wait<1>();
      if (kb > 0 && (tid & 127) == 0) mbar_arrive(bar0 + 64 + 8 * ((it - 1) % K4_STAGES));
    }
    wg_wait<0>();
    if ((tid & 127) == 0) mbar_arrive(bar0 + 64 + 8 * ((pass * 10 + 9) % K4_STAGES));
    reg_fence(acc);
#pragma unroll
    for (int i = 0; i < 8; i++) {
      const int col = nblk * 192 + pass * 64 + 8 * i + 2 * q;
      float r[4];
#pragma unroll
      for (int j = 0; j < 4; j++) {
        const float g = acc[4 * i + j], u = acc[32 + 4 * i + j];
        r[j] = g / (1.0f + __expf(-g)) * u;
      }
      *reinterpret_cast<uint32_t*>(g_act + (size_t)row * FF + col) = pack_bf16(r[0], r[1]);
      *reinterpret_cast<uint32_t*>(g_act + (size_t)(row + 8) * FF + col) = pack_bf16(r[2], r[3]);
    }
  }
}

typedef CUresult (*EncodeFn)(CUtensorMap*, CUtensorMapDataType, cuuint32_t, void*, const cuuint64_t*, const cuuint64_t*,
                             const cuuint32_t*, const cuuint32_t*, CUtensorMapInterleave, CUtensorMapSwizzle,
                             CUtensorMapL2promotion, CUtensorMapFloatOOBfill);
static void make_map(EncodeFn fn, CUtensorMap* m, const void* ptr, uint64_t cols, uint64_t rows, uint32_t bc, uint32_t br,
                     CUtensorMapSwizzle sw) {
  cuuint64_t dims[2] = {cols, rows};
  cuuint64_t strides[1] = {cols * 2};
  cuuint32_t box[2] = {bc, br};
  cuuint32_t es[2] = {1, 1};
  fn(m, CU_TENSOR_MAP_DATA_TYPE_BFLOAT16, 2, const_cast<void*>(ptr), dims, strides, box, es, CU_TENSOR_MAP_INTERLEAVE_NONE, sw,
     CU_TENSOR_MAP_L2_PROMOTION_L2_128B, CU_TENSOR_MAP_FLOAT_OOB_FILL_NONE);
}

extern "C" void kernel_launch(void* const* d_in, const int* in_sizes, int n_in, void* d_out, int out_size) {
  const bf16* x = (const bf16*)d_in[0];
  const bf16* wqkv = (const bf16*)d_in[1];
  const bf16* wo = (const bf16*)d_in[2];
  const bf16* wg = (const bf16*)d_in[4];
  const bf16* wu = (const bf16*)d_in[5];
  const bf16* wd = (const bf16*)d_in[6];
  bf16* out = (bf16*)d_out;
  static EncodeFn fn = nullptr;
  static void *p_qkv, *p_o, *p_h, *p_act;
  if (!fn) {
    void* f = nullptr;
    cudaDriverEntryPointQueryResult qr;
    cudaGetDriverEntryPoint("cuTensorMapEncodeTiled", &f, cudaEnableDefault, &qr);
    fn = (EncodeFn)f;
    cudaGetSymbolAddress(&p_qkv, g_qkv);
    cudaGetSymbolAddress(&p_o, g_o);
    cudaGetSymbolAddress(&p_h, g_h);
    cudaGetSymbolAddress(&p_act, g_act);
    cudaFuncSetAttribute(k1_ln_qkv, cudaFuncAttributeMaxDynamicSharedMemorySize, K1_SMEM);
    cudaFuncSetAttribute(k2_attn, cudaFuncAttributeMaxDynamicSharedMemorySize, K2_SMEM);
    cudaFuncSetAttribute(k_gemm_res<640>, cudaFuncAttributeMaxDynamicSharedMemorySize, G_SMEM);
    cudaFuncSetAttribute(k_gemm_res<1536>, cudaFuncAttributeMaxDynamicSharedMemorySize, G_SMEM);
    cudaFuncSetAttribute(k4_ln_ffn, cudaFuncAttributeMaxDynamicSharedMemorySize, K4_SMEM);
  }
  CUtensorMap mWqkv, mQKV, mO, mWo, mWg, mWu, mAct, mWd;
  make_map(fn, &mWqkv, wqkv, 3 * DM, DM, 64, 32, CU_TENSOR_MAP_SWIZZLE_128B);
  make_map(fn, &mQKV, p_qkv, 32, 3 * NH * SEQ, 32, 128, CU_TENSOR_MAP_SWIZZLE_64B);
  make_map(fn, &mO, p_o, DM, SEQ, 64, 128, CU_TENSOR_MAP_SWIZZLE_128B);
  make_map(fn, &mWo, wo, DM, DM, 64, 64, CU_TENSOR_MAP_SWIZZLE_128B);
  make_map(fn, &mWg, wg, FF, DM, 64, 64, CU_TENSOR_MAP_SWIZZLE_128B);
  make_map(fn, &mWu, wu, FF, DM, 64, 64, CU_TENSOR_MAP_SWIZZLE_128B);
  make_map(fn, &mAct, p_act, FF, SEQ, 64, 128, CU_TENSOR_MAP_SWIZZLE_128B);
  make_map(fn, &mWd, wd, DM, FF, 64, 64, CU_TENSOR_MAP_SWIZZLE_128B);
  k1_ln_qkv<<<128, 288, K1_SMEM>>>(x, mWqkv);
  k2_attn<<<256, 512, K2_SMEM>>>(mQKV);
  k_gemm_res<640><<<128, 288, G_SMEM>>>(mO, mWo, x, (bf16*)p_h);
  k4_ln_ffn<<<128, 288, K4_SMEM>>>(mWg, mWu);
  k_gemm_res<1536><<<128, 288, G_SMEM>>>(mAct, mWd, (const bf16*)p_h, out);
}
```

```cpp
#include <cuda_runtime.h>
#include <cuda_bf16.h>
#include <cuda.h>
#include <stdint.h>

typedef __nv_bfloat16 bf16;

constexpr int SEQ = 2048, DM = 640, NH = 32, DH = 20, FF = 1536;

__device__ __align__(1024) bf16 g_qkv[3 * NH * SEQ * 32];
__device__ __align__(1024) bf16 g_o[SEQ * DM];
__device__ __align__(1024) bf16 g_h[SEQ * DM];
__device__ __align__(1024) bf16 g_act[SEQ * FF];

__device__ __forceinline__ uint32_t smem_u32(const void* p) { return (uint32_t)__cvta_generic_to_shared(p); }
__device__ __forceinline__ void mbar_init(uint32_t bar, uint32_t count) {
  asm volatile("mbarrier.init.shared::cta.b64 [%0], %1;" :: "r"(bar), "r"(count) : "memory");
}
__device__ __forceinline__ void mbar_expect_tx(uint32_t bar, uint32_t bytes) {
  asm volatile("mbarrier.arrive.expect_tx.shared::cta.b64 _, [%0], %1;" :: "r"(bar), "r"(bytes) : "memory");
}
__device__ __forceinline__ void mbar_arrive(uint32_t bar) {
  asm volatile("mbarrier.arrive.shared::cta.b64 _, [%0];" :: "r"(bar) : "memory");
}
__device__ __forceinline__ void mbar_wait(uint32_t bar, uint32_t parity) {
  uint32_t done;
  uint32_t it = 0;
  do {
    asm volatile("{\n.reg .pred p;\nmbarrier.try_wait.parity.shared::cta.b64 p, [%1], %2;\nselp.u32 %0, 1, 0, p;\n}"
                 : "=r"(done) : "r"(bar), "r"(parity) : "memory");
    if (++it > 4000000u) __trap();
  } while (!done);
}
__device__ __forceinline__ void tma_load_2d(uint32_t dst, const CUtensorMap* map, int c0, int c1, uint32_t bar) {
  asm volatile("cp.async.bulk.tensor.2d.shared::cluster.global.mbarrier::complete_tx::bytes [%0], [%1, {%3, %4}], [%2];"
               :: "r"(dst), "l"((uint64_t)map), "r"(bar), "r"(c0), "r"(c1) : "memory");
}
__device__ __forceinline__ void fence_async_smem() { asm volatile("fence.proxy.async.shared::cta;" ::: "memory"); }
__device__ __forceinline__ void wg_fence() { asm volatile("wgmma.fence.sync.aligned;" ::: "memory"); }
__device__ __forceinline__ void wg_commit() { asm volatile("wgmma.commit_group.sync.aligned;" ::: "memory"); }
template <int N> __device__ __forceinline__ void wg_wait() { asm volatile("wgmma.wait_group.sync.aligned %0;" :: "n"(N) : "memory"); }
template <int N> __device__ __forceinline__ void reg_fence(float (&d)[N]) {
#pragma unroll
  for (int i = 0; i < N; i++) asm volatile("" : "+f"(d[i]) :: "memory");
}
__device__ __forceinline__ uint64_t make_desc(uint32_t addr, uint32_t lbo, uint32_t sbo, uint32_t swz) {
  return (uint64_t)((addr & 0x3FFFF) >> 4) | ((uint64_t)(lbo >> 4) << 16) | ((uint64_t)(sbo >> 4) << 32) | ((uint64_t)swz << 62);
}
__device__ __forceinline__ uint32_t pack_bf16(float a, float b) {
  __nv_bfloat162 v = __floats2bfloat162_rn(a, b);
  return *reinterpret_cast<uint32_t*>(&v);
}
__device__ __forceinline__ float ex2(float x) { float y; asm("ex2.approx.ftz.f32 %0, %1;" : "=f"(y) : "f"(x)); return y; }
__device__ __forceinline__ void named_bar_sync(int id, int n) { asm volatile("bar.sync %0, %1;" :: "r"(id), "r"(n) : "memory"); }

template<int TB> __device__ __forceinline__ void wgmma_ss_n240(float (&d)[120], uint64_t descA, uint64_t descB, int scaleD) {
  asm volatile("{\n.reg .pred p;\nsetp.ne.b32 p, %122, 0;\n"
    "wgmma.mma_async.sync.aligned.m64n240k16.f32.bf16.bf16 {%0, %1, %2, %3, %4, %5, %6, %7, %8, %9, %10, %11, %12, %13, %14, %15, %16, %17, %18, %19, %20, %21, %22, %23, %24, %25, %26, %27, %28, %29, %30, %31, %32, %33, %34, %35, %36, %37, %38, %39, %40, %41, %42, %43, %44, %45, %46, %47, %48, %49, %50, %51, %52, %53, %54, %55, %56, %57, %58, %59, %60, %61, %62, %63, %64, %65, %66, %67, %68, %69, %70, %71, %72, %73, %74, %75, %76, %77, %78, %79, %80, %81, %82, %83, %84, %85, %86, %87, %88, %89, %90, %91, %92, %93, %94, %95, %96, %97, %98, %99, %100, %101, %102, %103, %104, %105, %106, %107, %108, %109, %110, %111, %112, %113, %114, %115, %116, %117, %118, %119}, %120, %121, p, 1, 1, 0, %123;\n}"
    : "+f"(d[0]), "+f"(d[1]), "+f"(d[2]), "+f"(d[3]), "+f"(d[4]), "+f"(d[5]), "+f"(d[6]), "+f"(d[7]), "+f"(d[8]), "+f"(d[9]), "+f"(d[10]), "+f"(d[11]), "+f"(d[12]), "+f"(d[13]), "+f"(d[14]), "+f"(d[15]), "+f"(d[16]), "+f"(d[17]), "+f"(d[18]), "+f"(d[19]), "+f"(d[20]), "+f"(d[21]), "+f"(d[22]), "+f"(d[23]), "+f"(d[24]), "+f"(d[25]), "+f"(d[26]), "+f"(d[27]), "+f"(d[28]), "+f"(d[29]), "+f"(d[30]), "+f"(d[31]), "+f"(d[32]), "+f"(d[33]), "+f"(d[34]), "+f"(d[35]), "+f"(d[36]), "+f"(d[37]), "+f"(d[38]), "+f"(d[39]), "+f"(d[40]), "+f"(d[41]), "+f"(d[42]), "+f"(d[43]), "+f"(d[44]), "+f"(d[45]), "+f"(d[46]), "+f"(d[47]), "+f"(d[48]), "+f"(d[49]), "+f"(d[50]), "+f"(d[51]), "+f"(d[52]), "+f"(d[53]), "+f"(d[54]), "+f"(d[55]), "+f"(d[56]), "+f"(d[57]), "+f"(d[58]), "+f"(d[59]), "+f"(d[60]), "+f"(d[61]), "+f"(d[62]), "+f"(d[63]), "+f"(d[64]), "+f"(d[65]), "+f"(d[66]), "+f"(d[67]), "+f"(d[68]), "+f"(d[69]), "+f"(d[70]), "+f"(d[71]), "+f"(d[72]), "+f"(d[73]), "+f"(d[74]), "+f"(d[75]), "+f"(d[76]), "+f"(d[77]), "+f"(d[78]), "+f"(d[79]), "+f"(d[80]), "+f"(d[81]), "+f"(d[82]), "+f"(d[83]), "+f"(d[84]), "+f"(d[85]), "+f"(d[86]), "+f"(d[87]), "+f"(d[88]), "+f"(d[89]), "+f"(d[90]), "+f"(d[91]), "+f"(d[92]), "+f"(d[93]), "+f"(d[94]), "+f"(d[95]), "+f"(d[96]), "+f"(d[97]), "+f"(d[98]), "+f"(d[99]), "+f"(d[100]), "+f"(d[101]), "+f"(d[102]), "+f"(d[103]), "+f"(d[104]), "+f"(d[105]), "+f"(d[106]), "+f"(d[107]), "+f"(d[108]), "+f"(d[109]), "+f"(d[110]), "+f"(d[111]), "+f"(d[112]), "+f"(d[113]), "+f"(d[114]), "+f"(d[115]), "+f"(d[116]), "+f"(d[117]), "+f"(d[118]), "+f"(d[119])
    : "l"(descA), "l"(descB), "r"(scaleD), "n"(TB));
}
template<int TB> __device__ __forceinline__ void wgmma_ss_n128(float (&d)[64], uint64_t descA, uint64_t descB, int scaleD) {
  asm volatile("{\n.reg .pred p;\nsetp.ne.b32 p, %66, 0;\n"
    "wgmma.mma_async.sync.aligned.m64n128k16.f32.bf16.bf16 {%0, %1, %2, %3, %4, %5, %6, %7, %8, %9, %10, %11, %12, %13, %14, %15, %16, %17, %18, %19, %20, %21, %22, %23, %24, %25, %26, %27, %28, %29, %30, %31, %32, %33, %34, %35, %36, %37, %38, %39, %40, %41, %42, %43, %44, %45, %46, %47, %48, %49, %50, %51, %52, %53, %54, %55, %56, %57, %58, %59, %60, %61, %62, %63}, %64, %65, p, 1, 1, 0, %67;\n}"
    : "+f"(d[0]), "+f"(d[1]), "+f"(d[2]), "+f"(d[3]), "+f"(d[4]), "+f"(d[5]), "+f"(d[6]), "+f"(d[7]), "+f"(d[8]), "+f"(d[9]), "+f"(d[10]), "+f"(d[11]), "+f"(d[12]), "+f"(d[13]), "+f"(d[14]), "+f"(d[15]), "+f"(d[16]), "+f"(d[17]), "+f"(d[18]), "+f"(d[19]), "+f"(d[20]), "+f"(d[21]), "+f"(d[22]), "+f"(d[23]), "+f"(d[24]), "+f"(d[25]), "+f"(d[26]), "+f"(d[27]), "+f"(d[28]), "+f"(d[29]), "+f"(d[30]), "+f"(d[31]), "+f"(d[32]), "+f"(d[33]), "+f"(d[34]), "+f"(d[35]), "+f"(d[36]), "+f"(d[37]), "+f"(d[38]), "+f"(d[39]), "+f"(d[40]), "+f"(d[41]), "+f"(d[42]), "+f"(d[43]), "+f"(d[44]), "+f"(d[45]), "+f"(d[46]), "+f"(d[47]), "+f"(d[48]), "+f"(d[49]), "+f"(d[50]), "+f"(d[51]), "+f"(d[52]), "+f"(d[53]), "+f"(d[54]), "+f"(d[55]), "+f"(d[56]), "+f"(d[57]), "+f"(d[58]), "+f"(d[59]), "+f"(d[60]), "+f"(d[61]), "+f"(d[62]), "+f"(d[63])
    : "l"(descA), "l"(descB), "r"(scaleD), "n"(TB));
}
template<int TB> __device__ __forceinline__ void wgmma_ss_n80(float (&d)[40], uint64_t descA, uint64_t descB, int scaleD) {
  asm volatile("{\n.reg .pred p;\nsetp.ne.b32 p, %42, 0;\n"
    "wgmma.mma_async.sync.aligned.m64n80k16.f32.bf16.bf16 {%0, %1, %2, %3, %4, %5, %6, %7, %8, %9, %10, %11, %12, %13, %14, %15, %16, %17, %18, %19, %20, %21, %22, %23, %24, %25, %26, %27, %28, %29, %30, %31, %32, %33, %34, %35, %36, %37, %38, %39}, %40, %41, p, 1, 1, 0, %43;\n}"
    : "+f"(d[0]), "+f"(d[1]), "+f"(d[2]), "+f"(d[3]), "+f"(d[4]), "+f"(d[5]), "+f"(d[6]), "+f"(d[7]), "+f"(d[8]), "+f"(d[9]), "+f"(d[10]), "+f"(d[11]), "+f"(d[12]), "+f"(d[13]), "+f"(d[14]), "+f"(d[15]), "+f"(d[16]), "+f"(d[17]), "+f"(d[18]), "+f"(d[19]), "+f"(d[20]), "+f"(d[21]), "+f"(d[22]), "+f"(d[23]), "+f"(d[24]), "+f"(d[25]), "+f"(d[26]), "+f"(d[27]), "+f"(d[28]), "+f"(d[29]), "+f"(d[30]), "+f"(d[31]), "+f"(d[32]), "+f"(d[33]), "+f"(d[34]), "+f"(d[35]), "+f"(d[36]), "+f"(d[37]), "+f"(d[38]), "+f"(d[39])
    : "l"(descA), "l"(descB), "r"(scaleD), "n"(TB));
}
template<int TB> __device__ __forceinline__ void wgmma_ss_n64(float (&d)[32], uint64_t descA, uint64_t descB, int scaleD) {
  asm volatile("{\n.reg .pred p;\nsetp.ne.b32 p, %34, 0;\n"
    "wgmma.mma_async.sync.aligned.m64n64k16.f32.bf16.bf16 {%0, %1, %2, %3, %4, %5, %6, %7, %8, %9, %10, %11, %12, %13, %14, %15, %16, %17, %18, %19, %20, %21, %22, %23, %24, %25, %26, %27, %28, %29, %30, %31}, %32, %33, p, 1, 1, 0, %35;\n}"
    : "+f"(d[0]), "+f"(d[1]), "+f"(d[2]), "+f"(d[3]), "+f"(d[4]), "+f"(d[5]), "+f"(d[6]), "+f"(d[7]), "+f"(d[8]), "+f"(d[9]), "+f"(d[10]), "+f"(d[11]), "+f"(d[12]), "+f"(d[13]), "+f"(d[14]), "+f"(d[15]), "+f"(d[16]), "+f"(d[17]), "+f"(d[18]), "+f"(d[19]), "+f"(d[20]), "+f"(d[21]), "+f"(d[22]), "+f"(d[23]), "+f"(d[24]), "+f"(d[25]), "+f"(d[26]), "+f"(d[27]), "+f"(d[28]), "+f"(d[29]), "+f"(d[30]), "+f"(d[31])
    : "l"(descA), "l"(descB), "r"(scaleD), "n"(TB));
}
template<int TB> __device__ __forceinline__ void wgmma_rs_n24(float (&d)[12], uint32_t a0, uint32_t a1, uint32_t a2, uint32_t a3, uint64_t descB, int scaleD) {
  asm volatile("{\n.reg .pred p;\nsetp.ne.b32 p, %17, 0;\n"
    "wgmma.mma_async.sync.aligned.m64n24k16.f32.bf16.bf16 {%0, %1, %2, %3, %4, %5, %6, %7, %8, %9, %10, %11}, {%12, %13, %14, %15}, %16, p, 1, 1, %18;\n}"
    : "+f"(d[0]), "+f"(d[1]), "+f"(d[2]), "+f"(d[3]), "+f"(d[4]), "+f"(d[5]), "+f"(d[6]), "+f"(d[7]), "+f"(d[8]), "+f"(d[9]), "+f"(d[10]), "+f"(d[11])
    : "r"(a0), "r"(a1), "r"(a2), "r"(a3), "l"(descB), "r"(scaleD), "n"(TB));
}


__device__ __forceinline__ void ln_prologue(const bf16* __restrict__ src, int row0, uint8_t* sA, int ctid) {
  const int warp = ctid >> 5, lane = ctid & 31;
  for (int rr = 0; rr < 16; rr += 8) {
    uint2 v[8][5];
#pragma unroll
    for (int u = 0; u < 8; u++) {
      const uint2* p = reinterpret_cast<const uint2*>(src + (size_t)(row0 + warp * 16 + rr + u) * DM);
#pragma unroll
      for (int j = 0; j < 5; j++) v[u][j] = p[lane + 32 * j];
    }
#pragma unroll
    for (int u = 0; u < 8; u++) {
      float f[20];
#pragma unroll
      for (int j = 0; j < 5; j++) {
        f[4 * j + 0] = __uint_as_float(v[u][j].x << 16);
        f[4 * j + 1] = __uint_as_float(v[u][j].x & 0xffff0000u);
        f[4 * j + 2] = __uint_as_float(v[u][j].y << 16);
        f[4 * j + 3] = __uint_as_float(v[u][j].y & 0xffff0000u);
      }
      float s = 0.f;
#pragma unroll
      for (int j = 0; j < 20; j++) s += f[j];
#pragma unroll
      for (int o = 16; o > 0; o >>= 1) s += __shfl_xor_sync(0xffffffffu, s, o);
      const float mean = s * (1.0f / DM);
      float q = 0.f;
#pragma unroll
      for (int j = 0; j < 20; j++) { f[j] -= mean; q += f[j] * f[j]; }
#pragma unroll
      for (int o = 16; o > 0; o >>= 1) q += __shfl_xor_sync(0xffffffffu, q, o);
      const float rstd = rsqrtf(q * (1.0f / DM) + 1e-5f);
      const int r = warp * 16 + rr + u;
#pragma unroll
      for (int j = 0; j < 5; j++) {
        const int e = (lane + 32 * j) * 4;
        const int kb = e >> 6;
        const int byte = (e & 63) * 2;
        const int chunk = byte >> 4;
        const int sw = ((chunk ^ (r & 7)) << 4) | (byte & 15);
        uint2 o;
        o.x = pack_bf16(f[4 * j + 0] * rstd, f[4 * j + 1] * rstd);
        o.y = pack_bf16(f[4 * j + 2] * rstd, f[4 * j + 3] * rstd);
        *reinterpret_cast<uint2*>(sA + kb * 16384 + r * 128 + sw) = o;
      }
    }
  }
}

constexpr int K1_STAGES = 4;
constexpr int K1_SMEM = 163840 + K1_STAGES * 16384 + 1024;
__global__ void __launch_bounds__(288, 1) k1_ln_qkv(const bf16* __restrict__ x, const __grid_constant__ CUtensorMap tmW) {
  extern __shared__ __align__(1024) uint8_t smem[];
  uint8_t* sA = smem;
  uint8_t* sB = smem + 163840;
  const uint32_t bar0 = smem_u32(smem + 163840 + K1_STAGES * 16384);
  const int tid = threadIdx.x;
  const int mblk = blockIdx.x >> 3, nblk = blockIdx.x & 7;
  if (tid == 0) {
    for (int s = 0; s < K1_STAGES; s++) { mbar_init(bar0 + 8 * s, 1); mbar_init(bar0 + 64 + 8 * s, 2); }
    asm volatile("fence.mbarrier_init.release.cluster;" ::: "memory");
  }
  __syncthreads();
  if (tid >= 256) {
    if (tid == 256) {
      for (int it = 0; it < 20; it++) {
        const int s = it % K1_STAGES;
        mbar_wait(bar0 + 64 + 8 * s, ((it / K1_STAGES) & 1) ^ 1);
        mbar_expect_tx(bar0 + 8 * s, 16384);
        for (int b = 0; b < 4; b++)
          tma_load_2d(smem_u32(sB + s * 16384 + b * 4096), &tmW, nblk * 240 + b * 64, it * 32, bar0 + 8 * s);
      }
    }
    return;
  }
  ln_prologue(x, mblk * 128, sA, tid);
  fence_async_smem();
  named_bar_sync(1, 256);
  const int wg = tid >> 7;
  float acc[120];
#pragma unroll
  for (int i = 0; i < 120; i++) acc[i] = 0.f;
  const uint32_t aBase = smem_u32(sA) + wg * 64 * 128;
  const uint32_t bBase = smem_u32(sB);
  for (int it = 0; it < 20; it++) {
    const int s = it % K1_STAGES;
    mbar_wait(bar0 + 8 * s, (it / K1_STAGES) & 1);
    wg_fence();
#pragma unroll
    for (int kk = 0; kk < 2; kk++) {
      uint64_t da = make_desc(aBase + (it >> 1) * 16384 + (it & 1) * 64 + kk * 32, 16, 1024, 1);
      uint64_t db = make_desc(bBase + s * 16384 + kk * 2048, 4096, 1024, 1);
      wgmma_ss_n240<1>(acc, da, db, 1);
    }
    wg_commit();
    wg_wait<1>();
    if (it > 0 && (tid & 127) == 0) mbar_arrive(bar0 + 64 + 8 * ((it - 1) % K1_STAGES));
  }
  wg_wait<0>();
  reg_fence(acc);
  named_bar_sync(2 + wg, 128);
  const int lane = tid & 31, q = lane & 3;
  const int r = ((tid & 127) >> 5) * 16 + (lane >> 2);
  uint8_t* stg = sA + wg * 8192;
#pragma unroll
  for (int i = 0; i < 30; i++) {
    const int col = 8 * i + 2 * q;
    const int sl = col / 20, d = col - sl * 20;
    uint8_t* p = stg + (sl >> 1) * 16384 + (sl & 1) * 4096 + r * 64 + d * 2;
    *reinterpret_cast<uint32_t*>(p) = pack_bf16(acc[4 * i], acc[4 * i + 1]);
    *reinterpret_cast<uint32_t*>(p + 512) = pack_bf16(acc[4 * i + 2], acc[4 * i + 3]);
  }
  for (int t = tid & 127; t < 64 * 12 * 3; t += 128) {
    const int part = t % 3, sl = (t / 3) % 12, rr = t / 36;
    uint2 val = make_uint2(0u, 0u);
    if (nblk * 12 + sl >= 64 && part == 0) val.x = 0x00003F80u;
    *reinterpret_cast<uint2*>(stg + (sl >> 1) * 16384 + (sl & 1) * 4096 + rr * 64 + 40 + part * 8) = val;
  }
  fence_async_smem();
  named_bar_sync(2 + wg, 128);
  if ((tid & 127) < 12) {
    const int sl = tid & 127;
    bf16* dst = g_qkv + ((size_t)(nblk * 12 + sl) * SEQ + mblk * 128 + wg * 64) * 32;
    asm volatile("cp.async.bulk.global.shared::cta.bulk_group [%0], [%1], 4096;" :: "l"(dst), "r"(smem_u32(stg + (sl >> 1) * 16384 + (sl & 1) * 4096)) : "memory");
    asm volatile("cp.async.bulk.commit_group;" ::: "memory");
    asm volatile("cp.async.bulk.wait_group.read 0;" ::: "memory");
  }
}

constexpr int K2_STAGES = 6;
constexpr int K2_SMEM = 16384 + K2_STAGES * 16384 + 1024;
__global__ void __launch_bounds__(512, 1) k2_attn(const __grid_constant__ CUtensorMap tmQKV) {
  extern __shared__ __align__(1024) uint8_t smem[];
  uint8_t* sQ = smem;
  uint8_t* sKV = smem + 16384;
  const uint32_t bar0 = smem_u32(smem + 16384 + K2_STAGES * 16384);
  const int tid = threadIdx.x;
  const int head = blockIdx.x >> 3, qblk = blockIdx.x & 7;
  if (tid == 0) {
    for (int s = 0; s < K2_STAGES; s++) { mbar_init(bar0 + 8 * s, 1); mbar_init(bar0 + 64 + 8 * s, 4); }
    mbar_init(bar0 + 128, 1);
    asm volatile("fence.mbarrier_init.release.cluster;" ::: "memory");
  }
  __syncthreads();
  if (tid == 0) {
    mbar_expect_tx(bar0 + 128, 16384);
    tma_load_2d(smem_u32(sQ), &tmQKV, 0, head * SEQ + qblk * 256, bar0 + 128);
    tma_load_2d(smem_u32(sQ) + 8192, &tmQKV, 0, head * SEQ + qblk * 256 + 128, bar0 + 128);
    for (int it = 0; it < K2_STAGES - 2; it++) {
      mbar_expect_tx(bar0 + 8 * it, 16384);
      tma_load_2d(smem_u32(sKV + it * 16384), &tmQKV, 0, (32 + head) * SEQ + it * 128, bar0 + 8 * it);
      tma_load_2d(smem_u32(sKV + it * 16384 + 8192), &tmQKV, 0, (64 + head) * SEQ + it * 128, bar0 + 8 * it);
    }
  }
  const int wg = tid >> 7, lane = tid & 31;
  const float c = 0.22360679774997896f * 1.4426950408889634f;
  float o[12];
#pragma unroll
  for (int i = 0; i < 12; i++) o[i] = 0.f;
  float m0 = -INFINITY, m1 = -INFINITY;
  const uint32_t qBase = smem_u32(sQ) + wg * 4096;
  mbar_wait(bar0 + 128, 0);
  float sa[32], sb[32];
  auto issue_qk = [&](float (&sc)[32], int hs) {
    const int it = hs >> 1, s = it % K2_STAGES;
    if ((hs & 1) == 0) mbar_wait(bar0 + 8 * s, (it / K2_STAGES) & 1);
    const uint32_t kBase = smem_u32(sKV + s * 16384) + (hs & 1) * 4096;
    wg_fence();
#pragma unroll
    for (int kk = 0; kk < 2; kk++)
      wgmma_ss_n64<0>(sc, make_desc(qBase + kk * 32, 16, 512, 2), make_desc(kBase + kk * 32, 16, 512, 2), kk);
    wg_commit();
  };
  auto soft_pv = [&](float (&sc)[32], int hs) {
    const int it = hs >> 1, s = it % K2_STAGES;
    const uint32_t vBase = smem_u32(sKV + s * 16384) + 8192 + (hs & 1) * 4096;
    reg_fence(sc); reg_fence(o);
    float mx0 = m0, mx1 = m1;
#pragma unroll
    for (int i = 0; i < 8; i++) {
      mx0 = fmaxf(mx0, fmaxf(sc[4 * i], sc[4 * i + 1]));
      mx1 = fmaxf(mx1, fmaxf(sc[4 * i + 2], sc[4 * i + 3]));
    }
    mx0 = fmaxf(mx0, __shfl_xor_sync(0xffffffffu, mx0, 1)); mx0 = fmaxf(mx0, __shfl_xor_sync(0xffffffffu, mx0, 2));
    mx1 = fmaxf(mx1, __shfl_xor_sync(0xffffffffu, mx1, 1)); mx1 = fmaxf(mx1, __shfl_xor_sync(0xffffffffu, mx1, 2));
    const float a0 = ex2((m0 - mx0) * c), a1 = ex2((m1 - mx1) * c);
    m0 = mx0; m1 = mx1;
    const float nb0 = -mx0 * c, nb1 = -mx1 * c;
    uint32_t p[16];
#pragma unroll
    for (int i = 0; i < 8; i++) {
      p[2 * i] = pack_bf16(ex2(fmaf(sc[4 * i], c, nb0)), ex2(fmaf(sc[4 * i + 1], c, nb0)));
      p[2 * i + 1] = pack_bf16(ex2(fmaf(sc[4 * i + 2], c, nb1)), ex2(fmaf(sc[4 * i + 3], c, nb1)));
    }
#pragma unroll
    for (int i = 0; i < 3; i++) { o[4 * i] *= a0; o[4 * i + 1] *= a0; o[4 * i + 2] *= a1; o[4 * i + 3] *= a1; }
    wg_fence();
#pragma unroll
    for (int kk = 0; kk < 4; kk++)
      wgmma_rs_n24<1>(o, p[4 * kk], p[4 * kk + 1], p[4 * kk + 2], p[4 * kk + 3], make_desc(vBase + kk * 1024, 16, 512, 2), 1);
    wg_commit();
  };
  issue_qk(sa, 0);
  for (int it = 0; it < 16; it++) {
    if (tid == 0 && it + K2_STAGES - 2 < 16) {
      const int n = it + K2_STAGES - 2, ns = n % K2_STAGES;
      mbar_wait(bar0 + 64 + 8 * ns, ((n / K2_STAGES) & 1) ^ 1);
      mbar_expect_tx(bar0 + 8 * ns, 16384);
      tma_load_2d(smem_u32(sKV + ns * 16384), &tmQKV, 0, (32 + head) * SEQ + n * 128, bar0 + 8 * ns);
      tma_load_2d(smem_u32(sKV + ns * 16384 + 8192), &tmQKV, 0, (64 + head) * SEQ + n * 128, bar0 + 8 * ns);
    }
    __syncwarp();
    issue_qk(sb, 2 * it + 1);
    wg_wait<1>();
    if (it > 0 && (tid & 127) == 0) mbar_arrive(bar0 + 64 + 8 * ((it - 1) % K2_STAGES));
    soft_pv(sa, 2 * it);
    if (it < 15) { issue_qk(sa, 2 * it + 2); wg_wait<1>(); } else { wg_wait<0>(); }
    soft_pv(sb, 2 * it + 1);
  }
  wg_wait<0>();
  reg_fence(o);
  const float l0 = __shfl_sync(0xffffffffu, o[8], (lane & ~3) | 2);
  const float l1 = __shfl_sync(0xffffffffu, o[10], (lane & ~3) | 2);
  const float i0 = 1.0f / l0, i1 = 1.0f / l1;
  const int q = lane & 3;
  const int row = qblk * 256 + wg * 64 + ((tid & 127) >> 5) * 16 + (lane >> 2);
#pragma unroll
  for (int i = 0; i < 3; i++) {
    const int d = 8 * i + 2 * q;
    if (d < 20) {
      *reinterpret_cast<uint32_t*>(g_o + (size_t)row * DM + head * 20 + d) = pack_bf16(o[4 * i] * i0, o[4 * i + 1] * i0);
      *reinterpret_cast<uint32_t*>(g_o + (size_t)(row + 8) * DM + head * 20 + d) = pack_bf16(o[4 * i + 2] * i1, o[4 * i + 3] * i1);
    }
  }
}

constexpr int G_STAGES = 6;
constexpr int G_STAGE_BYTES = 16384 + 16384;
constexpr int G_SMEM = G_STAGES * G_STAGE_BYTES + 1024;
template <int KTOT>
__global__ void __launch_bounds__(288, 1) k_gemm_res(const __grid_constant__ CUtensorMap tmA, const __grid_constant__ CUtensorMap tmB,
                                                     const bf16* __restrict__ res, bf16* __restrict__ out) {
  extern __shared__ __align__(1024) uint8_t smem[];
  const uint32_t bar0 = smem_u32(smem + G_STAGES * G_STAGE_BYTES);
  const int tid = threadIdx.x;
  const int mblk = blockIdx.x >> 3, nblk = blockIdx.x & 7;
  constexpr int NIT = KTOT / 64;
  if (tid == 0) {
    for (int s = 0; s < G_STAGES; s++) { mbar_init(bar0 + 8 * s, 1); mbar_init(bar0 + 64 + 8 * s, 2); }
    asm volatile("fence.mbarrier_init.release.cluster;" ::: "memory");
  }
  __syncthreads();
  if (tid >= 256) {
    if (tid == 256) {
      for (int it = 0; it < NIT; it++) {
        const int s = it % G_STAGES;
        mbar_wait(bar0 + 64 + 8 * s, ((it / G_STAGES) & 1) ^ 1);
        mbar_expect_tx(bar0 + 8 * s, G_STAGE_BYTES);
        const uint32_t st = smem_u32(smem + s * G_STAGE_BYTES);
        tma_load_2d(st, &tmA, it * 64, mblk * 128, bar0 + 8 * s);
        tma_load_2d(st + 16384, &tmB, nblk * 80, it * 64, bar0 + 8 * s);
        tma_load_2d(st + 16384 + 8192, &tmB, nblk * 80 + 64, it * 64, bar0 + 8 * s);
      }
    }
    return;
  }
  const int wg = tid >> 7;
  float acc[40];
#pragma unroll
  for (int i = 0; i < 40; i++) acc[i] = 0.f;
  for (int it = 0; it < NIT; it++) {
    const int s = it % G_STAGES;
    const uint32_t st = smem_u32(smem + s * G_STAGE_BYTES);
    mbar_wait(bar0 + 8 * s, (it / G_STAGES) & 1);
    wg_fence();
#pragma unroll
    for (int kk = 0; kk < 4; kk++) {
      uint64_t da = make_desc(st + wg * 8192 + kk * 32, 16, 1024, 1);
      uint64_t db = make_desc(st + 16384 + kk * 2048, 8192, 1024, 1);
      wgmma_ss_n80<1>(acc, da, db, 1);
    }
    wg_commit();
    wg_wait<1>();
    if (it > 0 && (tid & 127) == 0) mbar_arrive(bar0 + 64 + 8 * ((it - 1) % G_STAGES));
  }
  wg_wait<0>();
  reg_fence(acc);
  const int lane = tid & 31, q = lane & 3;
  const int row = mblk * 128 + wg * 64 + ((tid & 127) >> 5) * 16 + (lane >> 2);
#pragma unroll
  for (int i = 0; i < 10; i++) {
    const int col = nblk * 80 + 8 * i + 2 * q;
    const uint32_t r0 = *reinterpret_cast<const uint32_t*>(res + (size_t)row * DM + col);
    const uint32_t r1 = *reinterpret_cast<const uint32_t*>(res + (size_t)(row + 8) * DM + col);
    *reinterpret_cast<uint32_t*>(out + (size_t)row * DM + col) =
        pack_bf16(acc[4 * i] + __uint_as_float(r0 << 16), acc[4 * i + 1] + __uint_as_float(r0 & 0xffff0000u));
    *reinterpret_cast<uint32_t*>(out + (size_t)(row + 8) * DM + col) =
        pack_bf16(acc[4 * i + 2] + __uint_as_float(r1 << 16), acc[4 * i + 3] + __uint_as_float(r1 & 0xffff0000u));
  }
}

constexpr int K4_STAGES = 4;
constexpr int K4_SMEM = 163840 + K4_STAGES * 16384 + 1024;
__global__ void __launch_bounds__(288, 1) k4_ln_ffn(const __grid_constant__ CUtensorMap tmG, const __grid_constant__ CUtensorMap tmU) {
  extern __shared__ __align__(1024) uint8_t smem[];
  uint8_t* sA = smem;
  uint8_t* sB = smem + 163840;
  const uint32_t bar0 = smem_u32(smem + 163840 + K4_STAGES * 16384);
  const int tid = threadIdx.x;
  const int mblk = blockIdx.x >> 3, nblk = blockIdx.x & 7;
  if (tid == 0) {
    for (int s = 0; s < K4_STAGES; s++) { mbar_init(bar0 + 8 * s, 1); mbar_init(bar0 + 64 + 8 * s, 2); }
    asm volatile("fence.mbarrier_init.release.cluster;" ::: "memory");
  }
  __syncthreads();
  if (tid >= 256) {
    if (tid == 256) {
      for (int it = 0; it < 30; it++) {
        const int s = it % K4_STAGES;
        const int pass = it / 10, kb = it % 10;
        mbar_wait(bar0 + 64 + 8 * s, ((it / K4_STAGES) & 1) ^ 1);
        mbar_expect_tx(bar0 + 8 * s, 16384);
        tma_load_2d(smem_u32(sB + s * 16384), &tmG, nblk * 192 + pass * 64, kb * 64, bar0 + 8 * s);
        tma_load_2d(smem_u32(sB + s * 16384 + 8192), &tmU, nblk * 192 + pass * 64, kb * 64, bar0 + 8 * s);
      }
    }
    return;
  }
  ln_prologue(g_h, mblk * 128, sA, tid);
  fence_async_smem();
  named_bar_sync(1, 256);
  const int wg = tid >> 7;
  const uint32_t aBase = smem_u32(sA) + wg * 64 * 128;
  const uint32_t bBase = smem_u32(sB);
  const int lane = tid & 31, q = lane & 3;
  const int row = mblk * 128 + wg * 64 + ((tid & 127) >> 5) * 16 + (lane >> 2);
  for (int pass = 0; pass < 3; pass++) {
    float acc[64];
#pragma unroll
    for (int i = 0; i < 64; i++) acc[i] = 0.f;
    for (int kb = 0; kb < 10; kb++) {
      const int it = pass * 10 + kb;
      const int s = it % K4_STAGES;
      mbar_wait(bar0 + 8 * s, (it / K4_STAGES) & 1);
      wg_fence();
#pragma unroll
      for (int kk = 0; kk < 4; kk++) {
        uint64_t da = make_desc(aBase + kb * 16384 + kk * 32, 16, 1024, 1);
        uint64_t db = make_desc(bBase + s * 16384 + kk * 2048, 8192, 1024, 1);
        wgmma_ss_n128<1>(acc, da, db, 1);
      }
      wg_commit();
      wg_wait<1>();
      if (kb > 0 && (tid & 127) == 0) mbar_arrive(bar0 + 64 + 8 * ((it - 1) % K4_STAGES));
    }
    wg_wait<0>();
    if ((tid & 127) == 0) mbar_arrive(bar0 + 64 + 8 * ((pass * 10 + 9) % K4_STAGES));
    reg_fence(acc);
#pragma unroll
    for (int i = 0; i < 8; i++) {
      const int col = nblk * 192 + pass * 64 + 8 * i + 2 * q;
      float r[4];
#pragma unroll
      for (int j = 0; j < 4; j++) {
        const float g = acc[4 * i + j], u = acc[32 + 4 * i + j];
        r[j] = g / (1.0f + __expf(-g)) * u;
      }
      *reinterpret_cast<uint32_t*>(g_act + (size_t)row * FF + col) = pack_bf16(r[0], r[1]);
      *reinterpret_cast<uint32_t*>(g_act + (size_t)(row + 8) * FF + col) = pack_bf16(r[2], r[3]);
    }
  }
}

typedef CUresult (*EncodeFn)(CUtensorMap*, CUtensorMapDataType, cuuint32_t, void*, const cuuint64_t*, const cuuint64_t*,
                             const cuuint32_t*, const cuuint32_t*, CUtensorMapInterleave, CUtensorMapSwizzle,
                             CUtensorMapL2promotion, CUtensorMapFloatOOBfill);
static void make_map(EncodeFn fn, CUtensorMap* m, const void* ptr, uint64_t cols, uint64_t rows, uint32_t bc, uint32_t br,
                     CUtensorMapSwizzle sw) {
  cuuint64_t dims[2] = {cols, rows};
  cuuint64_t strides[1] = {cols * 2};
  cuuint32_t box[2] = {bc, br};
  cuuint32_t es[2] = {1, 1};
  fn(m, CU_TENSOR_MAP_DATA_TYPE_BFLOAT16, 2, const_cast<void*>(ptr), dims, strides, box, es, CU_TENSOR_MAP_INTERLEAVE_NONE, sw,
     CU_TENSOR_MAP_L2_PROMOTION_L2_128B, CU_TENSOR_MAP_FLOAT_OOB_FILL_NONE);
}

extern "C" void kernel_launch(void* const* d_in, const int* in_sizes, int n_in, void* d_out, int out_size) {
  const bf16* x = (const bf16*)d_in[0];
  const bf16* wqkv = (const bf16*)d_in[1];
  const bf16* wo = (const bf16*)d_in[2];
  const bf16* wg = (const bf16*)d_in[4];
  const bf16* wu = (const bf16*)d_in[5];
  const bf16* wd = (const bf16*)d_in[6];
  bf16* out = (bf16*)d_out;
  static EncodeFn fn = nullptr;
  static void *p_qkv, *p_o, *p_h, *p_act;
  if (!fn) {
    void* f = nullptr;
    cudaDriverEntryPointQueryResult qr;
    cudaGetDriverEntryPoint("cuTensorMapEncodeTiled", &f, cudaEnableDefault, &qr);
    fn = (EncodeFn)f;
    cudaGetSymbolAddress(&p_qkv, g_qkv);
    cudaGetSymbolAddress(&p_o, g_o);
    cudaGetSymbolAddress(&p_h, g_h);
    cudaGetSymbolAddress(&p_act, g_act);
    cudaFuncSetAttribute(k1_ln_qkv, cudaFuncAttributeMaxDynamicSharedMemorySize, K1_SMEM);
    cudaFuncSetAttribute(k2_attn, cudaFuncAttributeMaxDynamicSharedMemorySize, K2_SMEM);
    cudaFuncSetAttribute(k_gemm_res<640>, cudaFuncAttributeMaxDynamicSharedMemorySize, G_SMEM);
    cudaFuncSetAttribute(k_gemm_res<1536>, cudaFuncAttributeMaxDynamicSharedMemorySize, G_SMEM);
    cudaFuncSetAttribute(k4_ln_ffn, cudaFuncAttributeMaxDynamicSharedMemorySize, K4_SMEM);
  }
  CUtensorMap mWqkv, mQKV, mO, mWo, mWg, mWu, mAct, mWd;
  make_map(fn, &mWqkv, wqkv, 3 * DM, DM, 64, 32, CU_TENSOR_MAP_SWIZZLE_128B);
  make_map(fn, &mQKV, p_qkv, 32, 3 * NH * SEQ, 32, 128, CU_TENSOR_MAP_SWIZZLE_64B);
  make_map(fn, &mO, p_o, DM, SEQ, 64, 128, CU_TENSOR_MAP_SWIZZLE_128B);
  make_map(fn, &mWo, wo, DM, DM, 64, 64, CU_TENSOR_MAP_SWIZZLE_128B);
  make_map(fn, &mWg, wg, FF, DM, 64, 64, CU_TENSOR_MAP_SWIZZLE_128B);
  make_map(fn, &mWu, wu, FF, DM, 64, 64, CU_TENSOR_MAP_SWIZZLE_128B);
  make_map(fn, &mAct, p_act, FF, SEQ, 64, 128, CU_TENSOR_MAP_SWIZZLE_128B);
  make_map(fn, &mWd, wd, DM, FF, 64, 64, CU_TENSOR_MAP_SWIZZLE_128B);
  k1_ln_qkv<<<128, 288, K1_SMEM>>>(x, mWqkv);
  k2_attn<<<256, 512, K2_SMEM>>>(mQKV);
  k_gemm_res<640><<<128, 288, G_SMEM>>>(mO, mWo, x, (bf16*)p_h);
  k4_ln_ffn<<<128, 288, K4_SMEM>>>(mWg, mWu);
  k_gemm_res<1536><<<128, 288, G_SMEM>>>(mAct, mWd, (const bf16*)p_h, out);
}
```

```cpp
#include <cuda_runtime.h>
#include <cuda_bf16.h>
#include <cuda.h>
#include <stdint.h>

typedef __nv_bfloat16 bf16;

constexpr int SEQ = 2048, DM = 640, NH = 32, DH = 20, FF = 1536;

__device__ __align__(1024) bf16 g_qkv[3 * NH * SEQ * 32];
__device__ __align__(1024) bf16 g_o[SEQ * DM];
__device__ __align__(1024) bf16 g_h[SEQ * DM];
__device__ __align__(1024) bf16 g_act[SEQ * FF];

__device__ __forceinline__ uint32_t smem_u32(const void* p) { return (uint32_t)__cvta_generic_to_shared(p); }
__device__ __forceinline__ void mbar_init(uint32_t bar, uint32_t count) {
  asm volatile("mbarrier.init.shared::cta.b64 [%0], %1;" :: "r"(bar), "r"(count) : "memory");
}
__device__ __forceinline__ void mbar_expect_tx(uint32_t bar, uint32_t bytes) {
  asm volatile("mbarrier.arrive.expect_tx.shared::cta.b64 _, [%0], %1;" :: "r"(bar), "r"(bytes) : "memory");
}
__device__ __forceinline__ void mbar_arrive(uint32_t bar) {
  asm volatile("mbarrier.arrive.shared::cta.b64 _, [%0];" :: "r"(bar) : "memory");
}
__device__ __forceinline__ void mbar_wait(uint32_t bar, uint32_t parity) {
  uint32_t done;
  uint32_t it = 0;
  do {
    asm volatile("{\n.reg .pred p;\nmbarrier.try_wait.parity.shared::cta.b64 p, [%1], %2;\nselp.u32 %0, 1, 0, p;\n}"
                 : "=r"(done) : "r"(bar), "r"(parity) : "memory");
    if (++it > 4000000u) __trap();
  } while (!done);
}
__device__ __forceinline__ void tma_load_2d(uint32_t dst, const CUtensorMap* map, int c0, int c1, uint32_t bar) {
  asm volatile("cp.async.bulk.tensor.2d.shared::cluster.global.mbarrier::complete_tx::bytes [%0], [%1, {%3, %4}], [%2];"
               :: "r"(dst), "l"((uint64_t)map), "r"(bar), "r"(c0), "r"(c1) : "memory");
}
__device__ __forceinline__ void fence_async_smem() { asm volatile("fence.proxy.async.shared::cta;" ::: "memory"); }
__device__ __forceinline__ void wg_fence() { asm volatile("wgmma.fence.sync.aligned;" ::: "memory"); }
__device__ __forceinline__ void wg_commit() { asm volatile("wgmma.commit_group.sync.aligned;" ::: "memory"); }
template <int N> __device__ __forceinline__ void wg_wait() { asm volatile("wgmma.wait_group.sync.aligned %0;" :: "n"(N) : "memory"); }
template <int N> __device__ __forceinline__ void reg_fence(float (&d)[N]) {
#pragma unroll
  for (int i = 0; i < N; i++) asm volatile("" : "+f"(d[i]) :: "memory");
}
__device__ __forceinline__ uint64_t make_desc(uint32_t addr, uint32_t lbo, uint32_t sbo, uint32_t swz) {
  return (uint64_t)((addr & 0x3FFFF) >> 4) | ((uint64_t)(lbo >> 4) << 16) | ((uint64_t)(sbo >> 4) << 32) | ((uint64_t)swz << 62);
}
__device__ __forceinline__ uint32_t pack_bf16(float a, float b) {
  __nv_bfloat162 v = __floats2bfloat162_rn(a, b);
  return *reinterpret_cast<uint32_t*>(&v);
}
__device__ __forceinline__ float ex2(float x) { float y; asm("ex2.approx.ftz.f32 %0, %1;" : "=f"(y) : "f"(x)); return y; }
__device__ __forceinline__ void named_bar_sync(int id, int n) { asm volatile("bar.sync %0, %1;" :: "r"(id), "r"(n) : "memory"); }

template<int TB> __device__ __forceinline__ void wgmma_ss_n240(float (&d)[120], uint64_t descA, uint64_t descB, int scaleD) {
  asm volatile("{\n.reg .pred p;\nsetp.ne.b32 p, %122, 0;\n"
    "wgmma.mma_async.sync.aligned.m64n240k16.f32.bf16.bf16 {%0, %1, %2, %3, %4, %5, %6, %7, %8, %9, %10, %11, %12, %13, %14, %15, %16, %17, %18, %19, %20, %21, %22, %23, %24, %25, %26, %27, %28, %29, %30, %31, %32, %33, %34, %35, %36, %37, %38, %39, %40, %41, %42, %43, %44, %45, %46, %47, %48, %49, %50, %51, %52, %53, %54, %55, %56, %57, %58, %59, %60, %61, %62, %63, %64, %65, %66, %67, %68, %69, %70, %71, %72, %73, %74, %75, %76, %77, %78, %79, %80, %81, %82, %83, %84, %85, %86, %87, %88, %89, %90, %91, %92, %93, %94, %95, %96, %97, %98, %99, %100, %101, %102, %103, %104, %105, %106, %107, %108, %109, %110, %111, %112, %113, %114, %115, %116, %117, %118, %119}, %120, %121, p, 1, 1, 0, %123;\n}"
    : "+f"(d[0]), "+f"(d[1]), "+f"(d[2]), "+f"(d[3]), "+f"(d[4]), "+f"(d[5]), "+f"(d[6]), "+f"(d[7]), "+f"(d[8]), "+f"(d[9]), "+f"(d[10]), "+f"(d[11]), "+f"(d[12]), "+f"(d[13]), "+f"(d[14]), "+f"(d[15]), "+f"(d[16]), "+f"(d[17]), "+f"(d[18]), "+f"(d[19]), "+f"(d[20]), "+f"(d[21]), "+f"(d[22]), "+f"(d[23]), "+f"(d[24]), "+f"(d[25]), "+f"(d[26]), "+f"(d[27]), "+f"(d[28]), "+f"(d[29]), "+f"(d[30]), "+f"(d[31]), "+f"(d[32]), "+f"(d[33]), "+f"(d[34]), "+f"(d[35]), "+f"(d[36]), "+f"(d[37]), "+f"(d[38]), "+f"(d[39]), "+f"(d[40]), "+f"(d[41]), "+f"(d[42]), "+f"(d[43]), "+f"(d[44]), "+f"(d[45]), "+f"(d[46]), "+f"(d[47]), "+f"(d[48]), "+f"(d[49]), "+f"(d[50]), "+f"(d[51]), "+f"(d[52]), "+f"(d[53]), "+f"(d[54]), "+f"(d[55]), "+f"(d[56]), "+f"(d[57]), "+f"(d[58]), "+f"(d[59]), "+f"(d[60]), "+f"(d[61]), "+f"(d[62]), "+f"(d[63]), "+f"(d[64]), "+f"(d[65]), "+f"(d[66]), "+f"(d[67]), "+f"(d[68]), "+f"(d[69]), "+f"(d[70]), "+f"(d[71]), "+f"(d[72]), "+f"(d[73]), "+f"(d[74]), "+f"(d[75]), "+f"(d[76]), "+f"(d[77]), "+f"(d[78]), "+f"(d[79]), "+f"(d[80]), "+f"(d[81]), "+f"(d[82]), "+f"(d[83]), "+f"(d[84]), "+f"(d[85]), "+f"(d[86]), "+f"(d[87]), "+f"(d[88]), "+f"(d[89]), "+f"(d[90]), "+f"(d[91]), "+f"(d[92]), "+f"(d[93]), "+f"(d[94]), "+f"(d[95]), "+f"(d[96]), "+f"(d[97]), "+f"(d[98]), "+f"(d[99]), "+f"(d[100]), "+f"(d[101]), "+f"(d[102]), "+f"(d[103]), "+f"(d[104]), "+f"(d[105]), "+f"(d[106]), "+f"(d[107]), "+f"(d[108]), "+f"(d[109]), "+f"(d[110]), "+f"(d[111]), "+f"(d[112]), "+f"(d[113]), "+f"(d[114]), "+f"(d[115]), "+f"(d[116]), "+f"(d[117]), "+f"(d[118]), "+f"(d[119])
    : "l"(descA), "l"(descB), "r"(scaleD), "n"(TB));
}
template<int TB> __device__ __forceinline__ void wgmma_ss_n128(float (&d)[64], uint64_t descA, uint64_t descB, int scaleD) {
  asm volatile("{\n.reg .pred p;\nsetp.ne.b32 p, %66, 0;\n"
    "wgmma.mma_async.sync.aligned.m64n128k16.f32.bf16.bf16 {%0, %1, %2, %3, %4, %5, %6, %7, %8, %9, %10, %11, %12, %13, %14, %15, %16, %17, %18, %19, %20, %21, %22, %23, %24, %25, %26, %27, %28, %29, %30, %31, %32, %33, %34, %35, %36, %37, %38, %39, %40, %41, %42, %43, %44, %45, %46, %47, %48, %49, %50, %51, %52, %53, %54, %55, %56, %57, %58, %59, %60, %61, %62, %63}, %64, %65, p, 1, 1, 0, %67;\n}"
    : "+f"(d[0]), "+f"(d[1]), "+f"(d[2]), "+f"(d[3]), "+f"(d[4]), "+f"(d[5]), "+f"(d[6]), "+f"(d[7]), "+f"(d[8]), "+f"(d[9]), "+f"(d[10]), "+f"(d[11]), "+f"(d[12]), "+f"(d[13]), "+f"(d[14]), "+f"(d[15]), "+f"(d[16]), "+f"(d[17]), "+f"(d[18]), "+f"(d[19]), "+f"(d[20]), "+f"(d[21]), "+f"(d[22]), "+f"(d[23]), "+f"(d[24]), "+f"(d[25]), "+f"(d[26]), "+f"(d[27]), "+f"(d[28]), "+f"(d[29]), "+f"(d[30]), "+f"(d[31]), "+f"(d[32]), "+f"(d[33]), "+f"(d[34]), "+f"(d[35]), "+f"(d[36]), "+f"(d[37]), "+f"(d[38]), "+f"(d[39]), "+f"(d[40]), "+f"(d[41]), "+f"(d[42]), "+f"(d[43]), "+f"(d[44]), "+f"(d[45]), "+f"(d[46]), "+f"(d[47]), "+f"(d[48]), "+f"(d[49]), "+f"(d[50]), "+f"(d[51]), "+f"(d[52]), "+f"(d[53]), "+f"(d[54]), "+f"(d[55]), "+f"(d[56]), "+f"(d[57]), "+f"(d[58]), "+f"(d[59]), "+f"(d[60]), "+f"(d[61]), "+f"(d[62]), "+f"(d[63])
    : "l"(descA), "l"(descB), "r"(scaleD), "n"(TB));
}
template<int TB> __device__ __forceinline__ void wgmma_ss_n80(float (&d)[40], uint64_t descA, uint64_t descB, int scaleD) {
  asm volatile("{\n.reg .pred p;\nsetp.ne.b32 p, %42, 0;\n"
    "wgmma.mma_async.sync.aligned.m64n80k16.f32.bf16.bf16 {%0, %1, %2, %3, %4, %5, %6, %7, %8, %9, %10, %11, %12, %13, %14, %15, %16, %17, %18, %19, %20, %21, %22, %23, %24, %25, %26, %27, %28, %29, %30, %31, %32, %33, %34, %35, %36, %37, %38, %39}, %40, %41, p, 1, 1, 0, %43;\n}"
    : "+f"(d[0]), "+f"(d[1]), "+f"(d[2]), "+f"(d[3]), "+f"(d[4]), "+f"(d[5]), "+f"(d[6]), "+f"(d[7]), "+f"(d[8]), "+f"(d[9]), "+f"(d[10]), "+f"(d[11]), "+f"(d[12]), "+f"(d[13]), "+f"(d[14]), "+f"(d[15]), "+f"(d[16]), "+f"(d[17]), "+f"(d[18]), "+f"(d[19]), "+f"(d[20]), "+f"(d[21]), "+f"(d[22]), "+f"(d[23]), "+f"(d[24]), "+f"(d[25]), "+f"(d[26]), "+f"(d[27]), "+f"(d[28]), "+f"(d[29]), "+f"(d[30]), "+f"(d[31]), "+f"(d[32]), "+f"(d[33]), "+f"(d[34]), "+f"(d[35]), "+f"(d[36]), "+f"(d[37]), "+f"(d[38]), "+f"(d[39])
    : "l"(descA), "l"(descB), "r"(scaleD), "n"(TB));
}
template<int TB> __device__ __forceinline__ void wgmma_ss_n64(float (&d)[32], uint64_t descA, uint64_t descB, int scaleD) {
  asm volatile("{\n.reg .pred p;\nsetp.ne.b32 p, %34, 0;\n"
    "wgmma.mma_async.sync.aligned.m64n64k16.f32.bf16.bf16 {%0, %1, %2, %3, %4, %5, %6, %7, %8, %9, %10, %11, %12, %13, %14, %15, %16, %17, %18, %19, %20, %21, %22, %23, %24, %25, %26, %27, %28, %29, %30, %31}, %32, %33, p, 1, 1, 0, %35;\n}"
    : "+f"(d[0]), "+f"(d[1]), "+f"(d[2]), "+f"(d[3]), "+f"(d[4]), "+f"(d[5]), "+f"(d[6]), "+f"(d[7]), "+f"(d[8]), "+f"(d[9]), "+f"(d[10]), "+f"(d[11]), "+f"(d[12]), "+f"(d[13]), "+f"(d[14]), "+f"(d[15]), "+f"(d[16]), "+f"(d[17]), "+f"(d[18]), "+f"(d[19]), "+f"(d[20]), "+f"(d[21]), "+f"(d[22]), "+f"(d[23]), "+f"(d[24]), "+f"(d[25]), "+f"(d[26]), "+f"(d[27]), "+f"(d[28]), "+f"(d[29]), "+f"(d[30]), "+f"(d[31])
    : "l"(descA), "l"(descB), "r"(scaleD), "n"(TB));
}
template<int TB> __device__ __forceinline__ void wgmma_rs_n24(float (&d)[12], uint32_t a0, uint32_t a1, uint32_t a2, uint32_t a3, uint64_t descB, int scaleD) {
  asm volatile("{\n.reg .pred p;\nsetp.ne.b32 p, %17, 0;\n"
    "wgmma.mma_async.sync.aligned.m64n24k16.f32.bf16.bf16 {%0, %1, %2, %3, %4, %5, %6, %7, %8, %9, %10, %11}, {%12, %13, %14, %15}, %16, p, 1, 1, %18;\n}"
    : "+f"(d[0]), "+f"(d[1]), "+f"(d[2]), "+f"(d[3]), "+f"(d[4]), "+f"(d[5]), "+f"(d[6]), "+f"(d[7]), "+f"(d[8]), "+f"(d[9]), "+f"(d[10]), "+f"(d[11])
    : "r"(a0), "r"(a1), "r"(a2), "r"(a3), "l"(descB), "r"(scaleD), "n"(TB));
}


__device__ __forceinline__ void ln_prologue(const bf16* __restrict__ src, int row0, uint8_t* sA, int ctid) {
  const int warp = ctid >> 5, lane = ctid & 31;
  for (int rr = 0; rr < 16; rr += 8) {
    uint2 v[8][5];
#pragma unroll
    for (int u = 0; u < 8; u++) {
      const uint2* p = reinterpret_cast<const uint2*>(src + (size_t)(row0 + warp * 16 + rr + u) * DM);
#pragma unroll
      for (int j = 0; j < 5; j++) v[u][j] = p[lane + 32 * j];
    }
#pragma unroll
    for (int u = 0; u < 8; u++) {
      float f[20];
#pragma unroll
      for (int j = 0; j < 5; j++) {
        f[4 * j + 0] = __uint_as_float(v[u][j].x << 16);
        f[4 * j + 1] = __uint_as_float(v[u][j].x & 0xffff0000u);
        f[4 * j + 2] = __uint_as_float(v[u][j].y << 16);
        f[4 * j + 3] = __uint_as_float(v[u][j].y & 0xffff0000u);
      }
      float s = 0.f;
#pragma unroll
      for (int j = 0; j < 20; j++) s += f[j];
#pragma unroll
      for (int o = 16; o > 0; o >>= 1) s += __shfl_xor_sync(0xffffffffu, s, o);
      const float mean = s * (1.0f / DM);
      float q = 0.f;
#pragma unroll
      for (int j = 0; j < 20; j++) { f[j] -= mean; q += f[j] * f[j]; }
#pragma unroll
      for (int o = 16; o > 0; o >>= 1) q += __shfl_xor_sync(0xffffffffu, q, o);
      const float rstd = rsqrtf(q * (1.0f / DM) + 1e-5f);
      const int r = warp * 16 + rr + u;
#pragma unroll
      for (int j = 0; j < 5; j++) {
        const int e = (lane + 32 * j) * 4;
        const int kb = e >> 6;
        const int byte = (e & 63) * 2;
        const int chunk = byte >> 4;
        const int sw = ((chunk ^ (r & 7)) << 4) | (byte & 15);
        uint2 o;
        o.x = pack_bf16(f[4 * j + 0] * rstd, f[4 * j + 1] * rstd);
        o.y = pack_bf16(f[4 * j + 2] * rstd, f[4 * j + 3] * rstd);
        *reinterpret_cast<uint2*>(sA + kb * 16384 + r * 128 + sw) = o;
      }
    }
  }
}

constexpr int K1_STAGES = 4;
constexpr int K1_SMEM = 163840 + K1_STAGES * 16384 + 1024;
__global__ void __launch_bounds__(288, 1) k1_ln_qkv(const bf16* __restrict__ x, const __grid_constant__ CUtensorMap tmW) {
  extern __shared__ __align__(1024) uint8_t smem[];
  uint8_t* sA = smem;
  uint8_t* sB = smem + 163840;
  const uint32_t bar0 = smem_u32(smem + 163840 + K1_STAGES * 16384);
  const int tid = threadIdx.x;
  const int mblk = blockIdx.x >> 3, nblk = blockIdx.x & 7;
  if (tid == 0) {
    for (int s = 0; s < K1_STAGES; s++) { mbar_init(bar0 + 8 * s, 1); mbar_init(bar0 + 64 + 8 * s, 2); }
    asm volatile("fence.mbarrier_init.release.cluster;" ::: "memory");
  }
  __syncthreads();
  if (tid >= 256) {
    if (tid == 256) {
      for (int it = 0; it < 20; it++) {
        const int s = it % K1_STAGES;
        mbar_wait(bar0 + 64 + 8 * s, ((it / K1_STAGES) & 1) ^ 1);
        mbar_expect_tx(bar0 + 8 * s, 16384);
        for (int b = 0; b < 4; b++)
          tma_load_2d(smem_u32(sB + s * 16384 + b * 4096), &tmW, nblk * 240 + b * 64, it * 32, bar0 + 8 * s);
      }
    }
    return;
  }
  ln_prologue(x, mblk * 128, sA, tid);
  fence_async_smem();
  named_bar_sync(1, 256);
  const int wg = tid >> 7;
  float acc[120];
#pragma unroll
  for (int i = 0; i < 120; i++) acc[i] = 0.f;
  const uint32_t aBase = smem_u32(sA) + wg * 64 * 128;
  const uint32_t bBase = smem_u32(sB);
  for (int it = 0; it < 20; it++) {
    const int s = it % K1_STAGES;
    mbar_wait(bar0 + 8 * s, (it / K1_STAGES) & 1);
    wg_fence();
#pragma unroll
    for (int kk = 0; kk < 2; kk++) {
      uint64_t da = make_desc(aBase + (it >> 1) * 16384 + (it & 1) * 64 + kk * 32, 16, 1024, 1);
      uint64_t db = make_desc(bBase + s * 16384 + kk * 2048, 4096, 1024, 1);
      wgmma_ss_n240<1>(acc, da, db, 1);
    }
    wg_commit();
    wg_wait<1>();
    if (it > 0 && (tid & 127) == 0) mbar_arrive(bar0 + 64 + 8 * ((it - 1) % K1_STAGES));
  }
  wg_wait<0>();
  reg_fence(acc);
  named_bar_sync(2 + wg, 128);
  const int lane = tid & 31, q = lane & 3;
  const int r = ((tid & 127) >> 5) * 16 + (lane >> 2);
  uint8_t* stg = sA + wg * 8192;
#pragma unroll
  for (int i = 0; i < 30; i++) {
    const int col = 8 * i + 2 * q;
    const int sl = col / 20, d = col - sl * 20;
    uint8_t* p = stg + (sl >> 1) * 16384 + (sl & 1) * 4096 + r * 64 + d * 2;
    *reinterpret_cast<uint32_t*>(p) = pack_bf16(acc[4 * i], acc[4 * i + 1]);
    *reinterpret_cast<uint32_t*>(p + 512) = pack_bf16(acc[4 * i + 2], acc[4 * i + 3]);
  }
  for (int t = tid & 127; t < 64 * 12 * 3; t += 128) {
    const int part = t % 3, sl = (t / 3) % 12, rr = t / 36;
    uint2 val = make_uint2(0u, 0u);
    if (nblk * 12 + sl >= 64 && part == 0) val.x = 0x00003F80u;
    *reinterpret_cast<uint2*>(stg + (sl >> 1) * 16384 + (sl & 1) * 4096 + rr * 64 + 40 + part * 8) = val;
  }
  fence_async_smem();
  named_bar_sync(2 + wg, 128);
  if ((tid & 127) < 12) {
    const int sl = tid & 127;
    bf16* dst = g_qkv + ((size_t)(nblk * 12 + sl) * SEQ + mblk * 128 + wg * 64) * 32;
    asm volatile("cp.async.bulk.global.shared::cta.bulk_group [%0], [%1], 4096;" :: "l"(dst), "r"(smem_u32(stg + (sl >> 1) * 16384 + (sl & 1) * 4096)) : "memory");
    asm volatile("cp.async.bulk.commit_group;" ::: "memory");
    asm volatile("cp.async.bulk.wait_group.read 0;" ::: "memory");
  }
}

constexpr int K2_STAGES = 6;
constexpr int K2_SMEM = 16384 + K2_STAGES * 16384 + 1024;
__global__ void __launch_bounds__(512, 1) k2_attn(const __grid_constant__ CUtensorMap tmQKV) {
  extern __shared__ __align__(1024) uint8_t smem[];
  uint8_t* sQ = smem;
  uint8_t* sKV = smem + 16384;
  const uint32_t bar0 = smem_u32(smem + 16384 + K2_STAGES * 16384);
  const int tid = threadIdx.x;
  const int head = blockIdx.x >> 3, qblk = blockIdx.x & 7;
  if (tid == 0) {
    for (int s = 0; s < K2_STAGES; s++) { mbar_init(bar0 + 8 * s, 1); mbar_init(bar0 + 64 + 8 * s, 4); }
    mbar_init(bar0 + 128, 1);
    asm volatile("fence.mbarrier_init.release.cluster;" ::: "memory");
  }
  __syncthreads();
  if (tid == 0) {
    mbar_expect_tx(bar0 + 128, 16384);
    tma_load_2d(smem_u32(sQ), &tmQKV, 0, head * SEQ + qblk * 256, bar0 + 128);
    tma_load_2d(smem_u32(sQ) + 8192, &tmQKV, 0, head * SEQ + qblk * 256 + 128, bar0 + 128);
    for (int it = 0; it < K2_STAGES - 2; it++) {
      mbar_expect_tx(bar0 + 8 * it, 16384);
      tma_load_2d(smem_u32(sKV + it * 16384), &tmQKV, 0, (32 + head) * SEQ + it * 128, bar0 + 8 * it);
      tma_load_2d(smem_u32(sKV + it * 16384 + 8192), &tmQKV, 0, (64 + head) * SEQ + it * 128, bar0 + 8 * it);
    }
  }
  const int wg = tid >> 7, lane = tid & 31;
  const float c = 0.22360679774997896f * 1.4426950408889634f;
  float o[12];
#pragma unroll
  for (int i = 0; i < 12; i++) o[i] = 0.f;
  float m0 = -INFINITY, m1 = -INFINITY;
  const uint32_t qBase = smem_u32(sQ) + wg * 4096;
  mbar_wait(bar0 + 128, 0);
  float sa[32], sb[32], t[12], pa0 = 0.f, pa1 = 0.f;
#pragma unroll
  for (int i = 0; i < 12; i++) t[i] = 0.f;
  auto issue_qk = [&](float (&sc)[32], int hs) {
    const int it = hs >> 1, s = it % K2_STAGES;
    if ((hs & 1) == 0) mbar_wait(bar0 + 8 * s, (it / K2_STAGES) & 1);
    const uint32_t kBase = smem_u32(sKV + s * 16384) + (hs & 1) * 4096;
    wg_fence();
#pragma unroll
    for (int kk = 0; kk < 2; kk++)
      wgmma_ss_n64<0>(sc, make_desc(qBase + kk * 32, 16, 512, 2), make_desc(kBase + kk * 32, 16, 512, 2), kk);
    wg_commit();
  };
  auto soft_pv = [&](float (&sc)[32], int hs) {
    const int it = hs >> 1, s = it % K2_STAGES;
    const uint32_t vBase = smem_u32(sKV + s * 16384) + 8192 + (hs & 1) * 4096;
    reg_fence(sc); reg_fence(t);
#pragma unroll
    for (int i = 0; i < 3; i++) {
      o[4 * i] = fmaf(o[4 * i], pa0, t[4 * i]); o[4 * i + 1] = fmaf(o[4 * i + 1], pa0, t[4 * i + 1]);
      o[4 * i + 2] = fmaf(o[4 * i + 2], pa1, t[4 * i + 2]); o[4 * i + 3] = fmaf(o[4 * i + 3], pa1, t[4 * i + 3]);
    }
    float mx0 = m0, mx1 = m1;
#pragma unroll
    for (int i = 0; i < 8; i++) {
      mx0 = fmaxf(mx0, fmaxf(sc[4 * i], sc[4 * i + 1]));
      mx1 = fmaxf(mx1, fmaxf(sc[4 * i + 2], sc[4 * i + 3]));
    }
    mx0 = fmaxf(mx0, __shfl_xor_sync(0xffffffffu, mx0, 1)); mx0 = fmaxf(mx0, __shfl_xor_sync(0xffffffffu, mx0, 2));
    mx1 = fmaxf(mx1, __shfl_xor_sync(0xffffffffu, mx1, 1)); mx1 = fmaxf(mx1, __shfl_xor_sync(0xffffffffu, mx1, 2));
    const float a0 = ex2((m0 - mx0) * c), a1 = ex2((m1 - mx1) * c);
    m0 = mx0; m1 = mx1;
    const float nb0 = -mx0 * c, nb1 = -mx1 * c;
    uint32_t p[16];
#pragma unroll
    for (int i = 0; i < 8; i++) {
      p[2 * i] = pack_bf16(ex2(fmaf(sc[4 * i], c, nb0)), ex2(fmaf(sc[4 * i + 1], c, nb0)));
      p[2 * i + 1] = pack_bf16(ex2(fmaf(sc[4 * i + 2], c, nb1)), ex2(fmaf(sc[4 * i + 3], c, nb1)));
    }
    pa0 = a0; pa1 = a1;
    wg_fence();
#pragma unroll
    for (int kk = 0; kk < 4; kk++)
      wgmma_rs_n24<1>(t, p[4 * kk], p[4 * kk + 1], p[4 * kk + 2], p[4 * kk + 3], make_desc(vBase + kk * 1024, 16, 512, 2), kk);
    wg_commit();
  };
  issue_qk(sa, 0);
  for (int it = 0; it < 16; it++) {
    if (tid == 0 && it + K2_STAGES - 2 < 16) {
      const int n = it + K2_STAGES - 2, ns = n % K2_STAGES;
      mbar_wait(bar0 + 64 + 8 * ns, ((n / K2_STAGES) & 1) ^ 1);
      mbar_expect_tx(bar0 + 8 * ns, 16384);
      tma_load_2d(smem_u32(sKV + ns * 16384), &tmQKV, 0, (32 + head) * SEQ + n * 128, bar0 + 8 * ns);
      tma_load_2d(smem_u32(sKV + ns * 16384 + 8192), &tmQKV, 0, (64 + head) * SEQ + n * 128, bar0 + 8 * ns);
    }
    __syncwarp();
    issue_qk(sb, 2 * it + 1);
    wg_wait<1>();
    if (it > 0 && (tid & 127) == 0) mbar_arrive(bar0 + 64 + 8 * ((it - 1) % K2_STAGES));
    soft_pv(sa, 2 * it);
    if (it < 15) { issue_qk(sa, 2 * it + 2); wg_wait<1>(); } else { wg_wait<0>(); }
    soft_pv(sb, 2 * it + 1);
  }
  wg_wait<0>();
  reg_fence(t);
#pragma unroll
  for (int i = 0; i < 3; i++) {
    o[4 * i] = fmaf(o[4 * i], pa0, t[4 * i]); o[4 * i + 1] = fmaf(o[4 * i + 1], pa0, t[4 * i + 1]);
    o[4 * i + 2] = fmaf(o[4 * i + 2], pa1, t[4 * i + 2]); o[4 * i + 3] = fmaf(o[4 * i + 3], pa1, t[4 * i + 3]);
  }
  const float l0 = __shfl_sync(0xffffffffu, o[8], (lane & ~3) | 2);
  const float l1 = __shfl_sync(0xffffffffu, o[10], (lane & ~3) | 2);
  const float i0 = 1.0f / l0, i1 = 1.0f / l1;
  const int q = lane & 3;
  const int row = qblk * 256 + wg * 64 + ((tid & 127) >> 5) * 16 + (lane >> 2);
#pragma unroll
  for (int i = 0; i < 3; i++) {
    const int d = 8 * i + 2 * q;
    if (d < 20) {
      *reinterpret_cast<uint32_t*>(g_o + (size_t)row * DM + head * 20 + d) = pack_bf16(o[4 * i] * i0, o[4 * i + 1] * i0);
      *reinterpret_cast<uint32_t*>(g_o + (size_t)(row + 8) * DM + head * 20 + d) = pack_bf16(o[4 * i + 2] * i1, o[4 * i + 3] * i1);
    }
  }
}

constexpr int G_STAGES = 6;
constexpr int G_STAGE_BYTES = 16384 + 16384;
constexpr int G_SMEM = G_STAGES * G_STAGE_BYTES + 1024;
template <int KTOT>
__global__ void __launch_bounds__(288, 1) k_gemm_res(const __grid_constant__ CUtensorMap tmA, const __grid_constant__ CUtensorMap tmB,
                                                     const bf16* __restrict__ res, bf16* __restrict__ out) {
  extern __shared__ __align__(1024) uint8_t smem[];
  const uint32_t bar0 = smem_u32(smem + G_STAGES * G_STAGE_BYTES);
  const int tid = threadIdx.x;
  const int mblk = blockIdx.x >> 3, nblk = blockIdx.x & 7;
  constexpr int NIT = KTOT / 64;
  if (tid == 0) {
    for (int s = 0; s < G_STAGES; s++) { mbar_init(bar0 + 8 * s, 1); mbar_init(bar0 + 64 + 8 * s, 2); }
    asm volatile("fence.mbarrier_init.release.cluster;" ::: "memory");
  }
  __syncthreads();
  if (tid >= 256) {
    if (tid == 256) {
      for (int it = 0; it < NIT; it++) {
        const int s = it % G_STAGES;
        mbar_wait(bar0 + 64 + 8 * s, ((it / G_STAGES) & 1) ^ 1);
        mbar_expect_tx(bar0 + 8 * s, G_STAGE_BYTES);
        const uint32_t st = smem_u32(smem + s * G_STAGE_BYTES);
        tma_load_2d(st, &tmA, it * 64, mblk * 128, bar0 + 8 * s);
        tma_load_2d(st + 16384, &tmB, nblk * 80, it * 64, bar0 + 8 * s);
        tma_load_2d(st + 16384 + 8192, &tmB, nblk * 80 + 64, it * 64, bar0 + 8 * s);
      }
    }
    return;
  }
  const int wg = tid >> 7;
  float acc[40];
#pragma unroll
  for (int i = 0; i < 40; i++) acc[i] = 0.f;
  for (int it = 0; it < NIT; it++) {
    const int s = it % G_STAGES;
    const uint32_t st = smem_u32(smem + s * G_STAGE_BYTES);
    mbar_wait(bar0 + 8 * s, (it / G_STAGES) & 1);
    wg_fence();
#pragma unroll
    for (int kk = 0; kk < 4; kk++) {
      uint64_t da = make_desc(st + wg * 8192 + kk * 32, 16, 1024, 1);
      uint64_t db = make_desc(st + 16384 + kk * 2048, 8192, 1024, 1);
      wgmma_ss_n80<1>(acc, da, db, 1);
    }
    wg_commit();
    wg_wait<1>();
    if (it > 0 && (tid & 127) == 0) mbar_arrive(bar0 + 64 + 8 * ((it - 1) % G_STAGES));
  }
  wg_wait<0>();
  reg_fence(acc);
  const int lane = tid & 31, q = lane & 3;
  const int row = mblk * 128 + wg * 64 + ((tid & 127) >> 5) * 16 + (lane >> 2);
#pragma unroll
  for (int i = 0; i < 10; i++) {
    const int col = nblk * 80 + 8 * i + 2 * q;
    const uint32_t r0 = *reinterpret_cast<const uint32_t*>(res + (size_t)row * DM + col);
    const uint32_t r1 = *reinterpret_cast<const uint32_t*>(res + (size_t)(row + 8) * DM + col);
    *reinterpret_cast<uint32_t*>(out + (size_t)row * DM + col) =
        pack_bf16(acc[4 * i] + __uint_as_float(r0 << 16), acc[4 * i + 1] + __uint_as_float(r0 & 0xffff0000u));
    *reinterpret_cast<uint32_t*>(out + (size_t)(row + 8) * DM + col) =
        pack_bf16(acc[4 * i + 2] + __uint_as_float(r1 << 16), acc[4 * i + 3] + __uint_as_float(r1 & 0xffff0000u));
  }
}

constexpr int K4_STAGES = 4;
constexpr int K4_SMEM = 163840 + K4_STAGES * 16384 + 1024;
__global__ void __launch_bounds__(288, 1) k4_ln_ffn(const __grid_constant__ CUtensorMap tmG, const __grid_constant__ CUtensorMap tmU) {
  extern __shared__ __align__(1024) uint8_t smem[];
  uint8_t* sA = smem;
  uint8_t* sB = smem + 163840;
  const uint32_t bar0 = smem_u32(smem + 163840 + K4_STAGES * 16384);
  const int tid = threadIdx.x;
  const int mblk = blockIdx.x >> 3, nblk = blockIdx.x & 7;
  if (tid == 0) {
    for (int s = 0; s < K4_STAGES; s++) { mbar_init(bar0 + 8 * s, 1); mbar_init(bar0 + 64 + 8 * s, 2); }
    asm volatile("fence.mbarrier_init.release.cluster;" ::: "memory");
  }
  __syncthreads();
  if (tid >= 256) {
    if (tid == 256) {
      for (int it = 0; it < 30; it++) {
        const int s = it % K4_STAGES;
        const int pass = it / 10, kb = it % 10;
        mbar_wait(bar0 + 64 + 8 * s, ((it / K4_STAGES) & 1) ^ 1);
        mbar_expect_tx(bar0 + 8 * s, 16384);
        tma_load_2d(smem_u32(sB + s * 16384), &tmG, nblk * 192 + pass * 64, kb * 64, bar0 + 8 * s);
        tma_load_2d(smem_u32(sB + s * 16384 + 8192), &tmU, nblk * 192 + pass * 64, kb * 64, bar0 + 8 * s);
      }
    }
    return;
  }
  ln_prologue(g_h, mblk * 128, sA, tid);
  fence_async_smem();
  named_bar_sync(1, 256);
  const int wg = tid >> 7;
  const uint32_t aBase = smem_u32(sA) + wg * 64 * 128;
  const uint32_t bBase = smem_u32(sB);
  const int lane = tid & 31, q = lane & 3;
  const int row = mblk * 128 + wg * 64 + ((tid & 127) >> 5) * 16 + (lane >> 2);
  for (int pass = 0; pass < 3; pass++) {
    float acc[64];
#pragma unroll
    for (int i = 0; i < 64; i++) acc[i] = 0.f;
    for (int kb = 0; kb < 10; kb++) {
      const int it = pass * 10 + kb;
      const int s = it % K4_STAGES;
      mbar_wait(bar0 + 8 * s, (it / K4_STAGES) & 1);
      wg_fence();
#pragma unroll
      for (int kk = 0; kk < 4; kk++) {
        uint64_t da = make_desc(aBase + kb * 16384 + kk * 32, 16, 1024, 1);
        uint64_t db = make_desc(bBase + s * 16384 + kk * 2048, 8192, 1024, 1);
        wgmma_ss_n128<1>(acc, da, db, 1);
      }
      wg_commit();
      wg_wait<1>();
      if (kb > 0 && (tid & 127) == 0) mbar_arrive(bar0 + 64 + 8 * ((it - 1) % K4_STAGES));
    }
    wg_wait<0>();
    if ((tid & 127) == 0) mbar_arrive(bar0 + 64 + 8 * ((pass * 10 + 9) % K4_STAGES));
    reg_fence(acc);
#pragma unroll
    for (int i = 0; i < 8; i++) {
      const int col = nblk * 192 + pass * 64 + 8 * i + 2 * q;
      float r[4];
#pragma unroll
      for (int j = 0; j < 4; j++) {
        const float g = acc[4 * i + j], u = acc[32 + 4 * i + j];
        r[j] = g / (1.0f + __expf(-g)) * u;
      }
      *reinterpret_cast<uint32_t*>(g_act + (size_t)row * FF + col) = pack_bf16(r[0], r[1]);
      *reinterpret_cast<uint32_t*>(g_act + (size_t)(row + 8) * FF + col) = pack_bf16(r[2], r[3]);
    }
  }
}

typedef CUresult (*EncodeFn)(CUtensorMap*, CUtensorMapDataType, cuuint32_t, void*, const cuuint64_t*, const cuuint64_t*,
                             const cuuint32_t*, const cuuint32_t*, CUtensorMapInterleave, CUtensorMapSwizzle,
                             CUtensorMapL2promotion, CUtensorMapFloatOOBfill);
static void make_map(EncodeFn fn, CUtensorMap* m, const void* ptr, uint64_t cols, uint64_t rows, uint32_t bc, uint32_t br,
                     CUtensorMapSwizzle sw) {
  cuuint64_t dims[2] = {cols, rows};
  cuuint64_t strides[1] = {cols * 2};
  cuuint32_t box[2] = {bc, br};
  cuuint32_t es[2] = {1, 1};
  fn(m, CU_TENSOR_MAP_DATA_TYPE_BFLOAT16, 2, const_cast<void*>(ptr), dims, strides, box, es, CU_TENSOR_MAP_INTERLEAVE_NONE, sw,
     CU_TENSOR_MAP_L2_PROMOTION_L2_128B, CU_TENSOR_MAP_FLOAT_OOB_FILL_NONE);
}

extern "C" void kernel_launch(void* const* d_in, const int* in_sizes, int n_in, void* d_out, int out_size) {
  const bf16* x = (const bf16*)d_in[0];
  const bf16* wqkv = (const bf16*)d_in[1];
  const bf16* wo = (const bf16*)d_in[2];
  const bf16* wg = (const bf16*)d_in[4];
  const bf16* wu = (const bf16*)d_in[5];
  const bf16* wd = (const bf16*)d_in[6];
  bf16* out = (bf16*)d_out;
  static EncodeFn fn = nullptr;
  static void *p_qkv, *p_o, *p_h, *p_act;
  if (!fn) {
    void* f = nullptr;
    cudaDriverEntryPointQueryResult qr;
    cudaGetDriverEntryPoint("cuTensorMapEncodeTiled", &f, cudaEnableDefault, &qr);
    fn = (EncodeFn)f;
    cudaGetSymbolAddress(&p_qkv, g_qkv);
    cudaGetSymbolAddress(&p_o, g_o);
    cudaGetSymbolAddress(&p_h, g_h);
    cudaGetSymbolAddress(&p_act, g_act);
    cudaFuncSetAttribute(k1_ln_qkv, cudaFuncAttributeMaxDynamicSharedMemorySize, K1_SMEM);
    cudaFuncSetAttribute(k2_attn, cudaFuncAttributeMaxDynamicSharedMemorySize, K2_SMEM);
    cudaFuncSetAttribute(k_gemm_res<640>, cudaFuncAttributeMaxDynamicSharedMemorySize, G_SMEM);
    cudaFuncSetAttribute(k_gemm_res<1536>, cudaFuncAttributeMaxDynamicSharedMemorySize, G_SMEM);
    cudaFuncSetAttribute(k4_ln_ffn, cudaFuncAttributeMaxDynamicSharedMemorySize, K4_SMEM);
  }
  CUtensorMap mWqkv, mQKV, mO, mWo, mWg, mWu, mAct, mWd;
  make_map(fn, &mWqkv, wqkv, 3 * DM, DM, 64, 32, CU_TENSOR_MAP_SWIZZLE_128B);
  make_map(fn, &mQKV, p_qkv, 32, 3 * NH * SEQ, 32, 128, CU_TENSOR_MAP_SWIZZLE_64B);
  make_map(fn, &mO, p_o, DM, SEQ, 64, 128, CU_TENSOR_MAP_SWIZZLE_128B);
  make_map(fn, &mWo, wo, DM, DM, 64, 64, CU_TENSOR_MAP_SWIZZLE_128B);
  make_map(fn, &mWg, wg, FF, DM, 64, 64, CU_TENSOR_MAP_SWIZZLE_128B);
  make_map(fn, &mWu, wu, FF, DM, 64, 64, CU_TENSOR_MAP_SWIZZLE_128B);
  make_map(fn, &mAct, p_act, FF, SEQ, 64, 128, CU_TENSOR_MAP_SWIZZLE_128B);
  make_map(fn, &mWd, wd, DM, FF, 64, 64, CU_TENSOR_MAP_SWIZZLE_128B);
  k1_ln_qkv<<<128, 288, K1_SMEM>>>(x, mWqkv);
  k2_attn<<<256, 512, K2_SMEM>>>(mQKV);
  k_gemm_res<640><<<128, 288, G_SMEM>>>(mO, mWo, x, (bf16*)p_h);
  k4_ln_ffn<<<128, 288, K4_SMEM>>>(mWg, mWu);
  k_gemm_res<1536><<<128, 288, G_SMEM>>>(mAct, mWd, (const bf16*)p_h, out);
}
```

```cpp
#include <cuda_runtime.h>
#include <cuda_bf16.h>
#include <cuda.h>
#include <stdint.h>

typedef __nv_bfloat16 bf16;

constexpr int SEQ = 2048, DM = 640, NH = 32, DH = 20, FF = 1536;

__device__ __align__(1024) bf16 g_qkv[3 * NH * SEQ * 32];
__device__ __align__(1024) bf16 g_o[SEQ * DM];
__device__ __align__(1024) bf16 g_h[SEQ * DM];
__device__ __align__(1024) bf16 g_act[SEQ * FF];

__device__ __forceinline__ uint32_t smem_u32(const void* p) { return (uint32_t)__cvta_generic_to_shared(p); }
__device__ __forceinline__ void mbar_init(uint32_t bar, uint32_t count) {
  asm volatile("mbarrier.init.shared::cta.b64 [%0], %1;" :: "r"(bar), "r"(count) : "memory");
}
__device__ __forceinline__ void mbar_expect_tx(uint32_t bar, uint32_t bytes) {
  asm volatile("mbarrier.arrive.expect_tx.shared::cta.b64 _, [%0], %1;" :: "r"(bar), "r"(bytes) : "memory");
}
__device__ __forceinline__ void mbar_arrive(uint32_t bar) {
  asm volatile("mbarrier.arrive.shared::cta.b64 _, [%0];" :: "r"(bar) : "memory");
}
__device__ __forceinline__ void mbar_wait(uint32_t bar, uint32_t parity) {
  uint32_t done;
  uint32_t it = 0;
  do {
    asm volatile("{\n.reg .pred p;\nmbarrier.try_wait.parity.shared::cta.b64 p, [%1], %2;\nselp.u32 %0, 1, 0, p;\n}"
                 : "=r"(done) : "r"(bar), "r"(parity) : "memory");
    if (++it > 4000000u) __trap();
  } while (!done);
}
__device__ __forceinline__ void tma_load_2d(uint32_t dst, const CUtensorMap* map, int c0, int c1, uint32_t bar) {
  asm volatile("cp.async.bulk.tensor.2d.shared::cluster.global.mbarrier::complete_tx::bytes [%0], [%1, {%3, %4}], [%2];"
               :: "r"(dst), "l"((uint64_t)map), "r"(bar), "r"(c0), "r"(c1) : "memory");
}
__device__ __forceinline__ void fence_async_smem() { asm volatile("fence.proxy.async.shared::cta;" ::: "memory"); }
__device__ __forceinline__ void wg_fence() { asm volatile("wgmma.fence.sync.aligned;" ::: "memory"); }
__device__ __forceinline__ void wg_commit() { asm volatile("wgmma.commit_group.sync.aligned;" ::: "memory"); }
template <int N> __device__ __forceinline__ void wg_wait() { asm volatile("wgmma.wait_group.sync.aligned %0;" :: "n"(N) : "memory"); }
template <int N> __device__ __forceinline__ void reg_fence(float (&d)[N]) {
#pragma unroll
  for (int i = 0; i < N; i++) asm volatile("" : "+f"(d[i]) :: "memory");
}
__device__ __forceinline__ uint64_t make_desc(uint32_t addr, uint32_t lbo, uint32_t sbo, uint32_t swz) {
  return (uint64_t)((addr & 0x3FFFF) >> 4) | ((uint64_t)(lbo >> 4) << 16) | ((uint64_t)(sbo >> 4) << 32) | ((uint64_t)swz << 62);
}
__device__ __forceinline__ uint32_t pack_bf16(float a, float b) {
  __nv_bfloat162 v = __floats2bfloat162_rn(a, b);
  return *reinterpret_cast<uint32_t*>(&v);
}
__device__ __forceinline__ float ex2(float x) { float y; asm("ex2.approx.ftz.f32 %0, %1;" : "=f"(y) : "f"(x)); return y; }
__device__ __forceinline__ void named_bar_sync(int id, int n) { asm volatile("bar.sync %0, %1;" :: "r"(id), "r"(n) : "memory"); }

template<int TB> __device__ __forceinline__ void wgmma_ss_n240(float (&d)[120], uint64_t descA, uint64_t descB, int scaleD) {
  asm volatile("{\n.reg .pred p;\nsetp.ne.b32 p, %122, 0;\n"
    "wgmma.mma_async.sync.aligned.m64n240k16.f32.bf16.bf16 {%0, %1, %2, %3, %4, %5, %6, %7, %8, %9, %10, %11, %12, %13, %14, %15, %16, %17, %18, %19, %20, %21, %22, %23, %24, %25, %26, %27, %28, %29, %30, %31, %32, %33, %34, %35, %36, %37, %38, %39, %40, %41, %42, %43, %44, %45, %46, %47, %48, %49, %50, %51, %52, %53, %54, %55, %56, %57, %58, %59, %60, %61, %62, %63, %64, %65, %66, %67, %68, %69, %70, %71, %72, %73, %74, %75, %76, %77, %78, %79, %80, %81, %82, %83, %84, %85, %86, %87, %88, %89, %90, %91, %92, %93, %94, %95, %96, %97, %98, %99, %100, %101, %102, %103, %104, %105, %106, %107, %108, %109, %110, %111, %112, %113, %114, %115, %116, %117, %118, %119}, %120, %121, p, 1, 1, 0, %123;\n}"
    : "+f"(d[0]), "+f"(d[1]), "+f"(d[2]), "+f"(d[3]), "+f"(d[4]), "+f"(d[5]), "+f"(d[6]), "+f"(d[7]), "+f"(d[8]), "+f"(d[9]), "+f"(d[10]), "+f"(d[11]), "+f"(d[12]), "+f"(d[13]), "+f"(d[14]), "+f"(d[15]), "+f"(d[16]), "+f"(d[17]), "+f"(d[18]), "+f"(d[19]), "+f"(d[20]), "+f"(d[21]), "+f"(d[22]), "+f"(d[23]), "+f"(d[24]), "+f"(d[25]), "+f"(d[26]), "+f"(d[27]), "+f"(d[28]), "+f"(d[29]), "+f"(d[30]), "+f"(d[31]), "+f"(d[32]), "+f"(d[33]), "+f"(d[34]), "+f"(d[35]), "+f"(d[36]), "+f"(d[37]), "+f"(d[38]), "+f"(d[39]), "+f"(d[40]), "+f"(d[41]), "+f"(d[42]), "+f"(d[43]), "+f"(d[44]), "+f"(d[45]), "+f"(d[46]), "+f"(d[47]), "+f"(d[48]), "+f"(d[49]), "+f"(d[50]), "+f"(d[51]), "+f"(d[52]), "+f"(d[53]), "+f"(d[54]), "+f"(d[55]), "+f"(d[56]), "+f"(d[57]), "+f"(d[58]), "+f"(d[59]), "+f"(d[60]), "+f"(d[61]), "+f"(d[62]), "+f"(d[63]), "+f"(d[64]), "+f"(d[65]), "+f"(d[66]), "+f"(d[67]), "+f"(d[68]), "+f"(d[69]), "+f"(d[70]), "+f"(d[71]), "+f"(d[72]), "+f"(d[73]), "+f"(d[74]), "+f"(d[75]), "+f"(d[76]), "+f"(d[77]), "+f"(d[78]), "+f"(d[79]), "+f"(d[80]), "+f"(d[81]), "+f"(d[82]), "+f"(d[83]), "+f"(d[84]), "+f"(d[85]), "+f"(d[86]), "+f"(d[87]), "+f"(d[88]), "+f"(d[89]), "+f"(d[90]), "+f"(d[91]), "+f"(d[92]), "+f"(d[93]), "+f"(d[94]), "+f"(d[95]), "+f"(d[96]), "+f"(d[97]), "+f"(d[98]), "+f"(d[99]), "+f"(d[100]), "+f"(d[101]), "+f"(d[102]), "+f"(d[103]), "+f"(d[104]), "+f"(d[105]), "+f"(d[106]), "+f"(d[107]), "+f"(d[108]), "+f"(d[109]), "+f"(d[110]), "+f"(d[111]), "+f"(d[112]), "+f"(d[113]), "+f"(d[114]), "+f"(d[115]), "+f"(d[116]), "+f"(d[117]), "+f"(d[118]), "+f"(d[119])
    : "l"(descA), "l"(descB), "r"(scaleD), "n"(TB));
}
template<int TB> __device__ __forceinline__ void wgmma_ss_n128(float (&d)[64], uint64_t descA, uint64_t descB, int scaleD) {
  asm volatile("{\n.reg .pred p;\nsetp.ne.b32 p, %66, 0;\n"
    "wgmma.mma_async.sync.aligned.m64n128k16.f32.bf16.bf16 {%0, %1, %2, %3, %4, %5, %6, %7, %8, %9, %10, %11, %12, %13, %14, %15, %16, %17, %18, %19, %20, %21, %22, %23, %24, %25, %26, %27, %28, %29, %30, %31, %32, %33, %34, %35, %36, %37, %38, %39, %40, %41, %42, %43, %44, %45, %46, %47, %48, %49, %50, %51, %52, %53, %54, %55, %56, %57, %58, %59, %60, %61, %62, %63}, %64, %65, p, 1, 1, 0, %67;\n}"
    : "+f"(d[0]), "+f"(d[1]), "+f"(d[2]), "+f"(d[3]), "+f"(d[4]), "+f"(d[5]), "+f"(d[6]), "+f"(d[7]), "+f"(d[8]), "+f"(d[9]), "+f"(d[10]), "+f"(d[11]), "+f"(d[12]), "+f"(d[13]), "+f"(d[14]), "+f"(d[15]), "+f"(d[16]), "+f"(d[17]), "+f"(d[18]), "+f"(d[19]), "+f"(d[20]), "+f"(d[21]), "+f"(d[22]), "+f"(d[23]), "+f"(d[24]), "+f"(d[25]), "+f"(d[26]), "+f"(d[27]), "+f"(d[28]), "+f"(d[29]), "+f"(d[30]), "+f"(d[31]), "+f"(d[32]), "+f"(d[33]), "+f"(d[34]), "+f"(d[35]), "+f"(d[36]), "+f"(d[37]), "+f"(d[38]), "+f"(d[39]), "+f"(d[40]), "+f"(d[41]), "+f"(d[42]), "+f"(d[43]), "+f"(d[44]), "+f"(d[45]), "+f"(d[46]), "+f"(d[47]), "+f"(d[48]), "+f"(d[49]), "+f"(d[50]), "+f"(d[51]), "+f"(d[52]), "+f"(d[53]), "+f"(d[54]), "+f"(d[55]), "+f"(d[56]), "+f"(d[57]), "+f"(d[58]), "+f"(d[59]), "+f"(d[60]), "+f"(d[61]), "+f"(d[62]), "+f"(d[63])
    : "l"(descA), "l"(descB), "r"(scaleD), "n"(TB));
}
template<int TB> __device__ __forceinline__ void wgmma_ss_n80(float (&d)[40], uint64_t descA, uint64_t descB, int scaleD) {
  asm volatile("{\n.reg .pred p;\nsetp.ne.b32 p, %42, 0;\n"
    "wgmma.mma_async.sync.aligned.m64n80k16.f32.bf16.bf16 {%0, %1, %2, %3, %4, %5, %6, %7, %8, %9, %10, %11, %12, %13, %14, %15, %16, %17, %18, %19, %20, %21, %22, %23, %24, %25, %26, %27, %28, %29, %30, %31, %32, %33, %34, %35, %36, %37, %38, %39}, %40, %41, p, 1, 1, 0, %43;\n}"
    : "+f"(d[0]), "+f"(d[1]), "+f"(d[2]), "+f"(d[3]), "+f"(d[4]), "+f"(d[5]), "+f"(d[6]), "+f"(d[7]), "+f"(d[8]), "+f"(d[9]), "+f"(d[10]), "+f"(d[11]), "+f"(d[12]), "+f"(d[13]), "+f"(d[14]), "+f"(d[15]), "+f"(d[16]), "+f"(d[17]), "+f"(d[18]), "+f"(d[19]), "+f"(d[20]), "+f"(d[21]), "+f"(d[22]), "+f"(d[23]), "+f"(d[24]), "+f"(d[25]), "+f"(d[26]), "+f"(d[27]), "+f"(d[28]), "+f"(d[29]), "+f"(d[30]), "+f"(d[31]), "+f"(d[32]), "+f"(d[33]), "+f"(d[34]), "+f"(d[35]), "+f"(d[36]), "+f"(d[37]), "+f"(d[38]), "+f"(d[39])
    : "l"(descA), "l"(descB), "r"(scaleD), "n"(TB));
}
template<int TB> __device__ __forceinline__ void wgmma_ss_n64(float (&d)[32], uint64_t descA, uint64_t descB, int scaleD) {
  asm volatile("{\n.reg .pred p;\nsetp.ne.b32 p, %34, 0;\n"
    "wgmma.mma_async.sync.aligned.m64n64k16.f32.bf16.bf16 {%0, %1, %2, %3, %4, %5, %6, %7, %8, %9, %10, %11, %12, %13, %14, %15, %16, %17, %18, %19, %20, %21, %22, %23, %24, %25, %26, %27, %28, %29, %30, %31}, %32, %33, p, 1, 1, 0, %35;\n}"
    : "+f"(d[0]), "+f"(d[1]), "+f"(d[2]), "+f"(d[3]), "+f"(d[4]), "+f"(d[5]), "+f"(d[6]), "+f"(d[7]), "+f"(d[8]), "+f"(d[9]), "+f"(d[10]), "+f"(d[11]), "+f"(d[12]), "+f"(d[13]), "+f"(d[14]), "+f"(d[15]), "+f"(d[16]), "+f"(d[17]), "+f"(d[18]), "+f"(d[19]), "+f"(d[20]), "+f"(d[21]), "+f"(d[22]), "+f"(d[23]), "+f"(d[24]), "+f"(d[25]), "+f"(d[26]), "+f"(d[27]), "+f"(d[28]), "+f"(d[29]), "+f"(d[30]), "+f"(d[31])
    : "l"(descA), "l"(descB), "r"(scaleD), "n"(TB));
}
template<int TB> __device__ __forceinline__ void wgmma_rs_n24(float (&d)[12], uint32_t a0, uint32_t a1, uint32_t a2, uint32_t a3, uint64_t descB, int scaleD) {
  asm volatile("{\n.reg .pred p;\nsetp.ne.b32 p, %17, 0;\n"
    "wgmma.mma_async.sync.aligned.m64n24k16.f32.bf16.bf16 {%0, %1, %2, %3, %4, %5, %6, %7, %8, %9, %10, %11}, {%12, %13, %14, %15}, %16, p, 1, 1, %18;\n}"
    : "+f"(d[0]), "+f"(d[1]), "+f"(d[2]), "+f"(d[3]), "+f"(d[4]), "+f"(d[5]), "+f"(d[6]), "+f"(d[7]), "+f"(d[8]), "+f"(d[9]), "+f"(d[10]), "+f"(d[11])
    : "r"(a0), "r"(a1), "r"(a2), "r"(a3), "l"(descB), "r"(scaleD), "n"(TB));
}


__device__ __forceinline__ void ln_prologue(const bf16* __restrict__ src, int row0, uint8_t* sA, int ctid) {
  const int warp = ctid >> 5, lane = ctid & 31;
  for (int rr = 0; rr < 16; rr += 8) {
    uint2 v[8][5];
#pragma unroll
    for (int u = 0; u < 8; u++) {
      const uint2* p = reinterpret_cast<const uint2*>(src + (size_t)(row0 + warp * 16 + rr + u) * DM);
#pragma unroll
      for (int j = 0; j < 5; j++) v[u][j] = p[lane + 32 * j];
    }
#pragma unroll
    for (int u = 0; u < 8; u++) {
      float f[20];
#pragma unroll
      for (int j = 0; j < 5; j++) {
        f[4 * j + 0] = __uint_as_float(v[u][j].x << 16);
        f[4 * j + 1] = __uint_as_float(v[u][j].x & 0xffff0000u);
        f[4 * j + 2] = __uint_as_float(v[u][j].y << 16);
        f[4 * j + 3] = __uint_as_float(v[u][j].y & 0xffff0000u);
      }
      float s = 0.f;
#pragma unroll
      for (int j = 0; j < 20; j++) s += f[j];
#pragma unroll
      for (int o = 16; o > 0; o >>= 1) s += __shfl_xor_sync(0xffffffffu, s, o);
      const float mean = s * (1.0f / DM);
      float q = 0.f;
#pragma unroll
      for (int j = 0; j < 20; j++) { f[j] -= mean; q += f[j] * f[j]; }
#pragma unroll
      for (int o = 16; o > 0; o >>= 1) q += __shfl_xor_sync(0xffffffffu, q, o);
      const float rstd = rsqrtf(q * (1.0f / DM) + 1e-5f);
      const int r = warp * 16 + rr + u;
#pragma unroll
      for (int j = 0; j < 5; j++) {
        const int e = (lane + 32 * j) * 4;
        const int kb = e >> 6;
        const int byte = (e & 63) * 2;
        const int chunk = byte >> 4;
        const int sw = ((chunk ^ (r & 7)) << 4) | (byte & 15);
        uint2 o;
        o.x = pack_bf16(f[4 * j + 0] * rstd, f[4 * j + 1] * rstd);
        o.y = pack_bf16(f[4 * j + 2] * rstd, f[4 * j + 3] * rstd);
        *reinterpret_cast<uint2*>(sA + kb * 16384 + r * 128 + sw) = o;
      }
    }
  }
}

constexpr int K1_STAGES = 4;
constexpr int K1_SMEM = 163840 + K1_STAGES * 16384 + 1024;
__global__ void __launch_bounds__(288, 1) k1_ln_qkv(const bf16* __restrict__ x, const __grid_constant__ CUtensorMap tmW) {
  extern __shared__ __align__(1024) uint8_t smem[];
  uint8_t* sA = smem;
  uint8_t* sB = smem + 163840;
  const uint32_t bar0 = smem_u32(smem + 163840 + K1_STAGES * 16384);
  const int tid = threadIdx.x;
  const int mblk = blockIdx.x >> 3, nblk = blockIdx.x & 7;
  if (tid == 0) {
    for (int s = 0; s < K1_STAGES; s++) { mbar_init(bar0 + 8 * s, 1); mbar_init(bar0 + 64 + 8 * s, 2); }
    asm volatile("fence.mbarrier_init.release.cluster;" ::: "memory");
  }
  __syncthreads();
  if (tid >= 256) {
    if (tid == 256) {
      for (int it = 0; it < 20; it++) {
        const int s = it % K1_STAGES;
        mbar_wait(bar0 + 64 + 8 * s, ((it / K1_STAGES) & 1) ^ 1);
        mbar_expect_tx(bar0 + 8 * s, 16384);
        for (int b = 0; b < 4; b++)
          tma_load_2d(smem_u32(sB + s * 16384 + b * 4096), &tmW, nblk * 240 + b * 64, it * 32, bar0 + 8 * s);
      }
    }
    return;
  }
  ln_prologue(x, mblk * 128, sA, tid);
  fence_async_smem();
  named_bar_sync(1, 256);
  const int wg = tid >> 7;
  float acc[120];
#pragma unroll
  for (int i = 0; i < 120; i++) acc[i] = 0.f;
  const uint32_t aBase = smem_u32(sA) + wg * 64 * 128;
  const uint32_t bBase = smem_u32(sB);
  for (int it = 0; it < 20; it++) {
    const int s = it % K1_STAGES;
    mbar_wait(bar0 + 8 * s, (it / K1_STAGES) & 1);
    wg_fence();
#pragma unroll
    for (int kk = 0; kk < 2; kk++) {
      uint64_t da = make_desc(aBase + (it >> 1) * 16384 + (it & 1) * 64 + kk * 32, 16, 1024, 1);
      uint64_t db = make_desc(bBase + s * 16384 + kk * 2048, 4096, 1024, 1);
      wgmma_ss_n240<1>(acc, da, db, 1);
    }
    wg_commit();
    wg_wait<1>();
    if (it > 0 && (tid & 127) == 0) mbar_arrive(bar0 + 64 + 8 * ((it - 1) % K1_STAGES));
  }
  wg_wait<0>();
  reg_fence(acc);
  named_bar_sync(2 + wg, 128);
  const int lane = tid & 31, q = lane & 3;
  const int r = ((tid & 127) >> 5) * 16 + (lane >> 2);
  uint8_t* stg = sA + wg * 8192;
#pragma unroll
  for (int i = 0; i < 30; i++) {
    const int col = 8 * i + 2 * q;
    const int sl = col / 20, d = col - sl * 20;
    uint8_t* p = stg + (sl >> 1) * 16384 + (sl & 1) * 4096 + r * 64 + d * 2;
    *reinterpret_cast<uint32_t*>(p) = pack_bf16(acc[4 * i], acc[4 * i + 1]);
    *reinterpret_cast<uint32_t*>(p + 512) = pack_bf16(acc[4 * i + 2], acc[4 * i + 3]);
  }
  for (int t = tid & 127; t < 64 * 12 * 3; t += 128) {
    const int part = t % 3, sl = (t / 3) % 12, rr = t / 36;
    uint2 val = make_uint2(0u, 0u);
    if (nblk * 12 + sl >= 64 && part == 0) val.x = 0x00003F80u;
    *reinterpret_cast<uint2*>(stg + (sl >> 1) * 16384 + (sl & 1) * 4096 + rr * 64 + 40 + part * 8) = val;
  }
  fence_async_smem();
  named_bar_sync(2 + wg, 128);
  if ((tid & 127) < 12) {
    const int sl = tid & 127;
    bf16* dst = g_qkv + ((size_t)(nblk * 12 + sl) * SEQ + mblk * 128 + wg * 64) * 32;
    asm volatile("cp.async.bulk.global.shared::cta.bulk_group [%0], [%1], 4096;" :: "l"(dst), "r"(smem_u32(stg + (sl >> 1) * 16384 + (sl & 1) * 4096)) : "memory");
    asm volatile("cp.async.bulk.commit_group;" ::: "memory");
    asm volatile("cp.async.bulk.wait_group.read 0;" ::: "memory");
  }
}

constexpr int K2_STAGES = 6;
constexpr int K2_SMEM = 16384 + K2_STAGES * 16384 + 1024;
__global__ void __launch_bounds__(512, 1) k2_attn(const __grid_constant__ CUtensorMap tmQKV) {
  extern __shared__ __align__(1024) uint8_t smem[];
  uint8_t* sQ = smem;
  uint8_t* sKV = smem + 16384;
  const uint32_t bar0 = smem_u32(smem + 16384 + K2_STAGES * 16384);
  const int tid = threadIdx.x;
  const int head = blockIdx.x >> 3, qblk = blockIdx.x & 7;
  if (tid == 0) {
    for (int s = 0; s < K2_STAGES; s++) { mbar_init(bar0 + 8 * s, 1); mbar_init(bar0 + 64 + 8 * s, 4); }
    mbar_init(bar0 + 128, 1);
    asm volatile("fence.mbarrier_init.release.cluster;" ::: "memory");
  }
  __syncthreads();
  if (tid == 0) {
    mbar_expect_tx(bar0 + 128, 16384);
    tma_load_2d(smem_u32(sQ), &tmQKV, 0, head * SEQ + qblk * 256, bar0 + 128);
    tma_load_2d(smem_u32(sQ) + 8192, &tmQKV, 0, head * SEQ + qblk * 256 + 128, bar0 + 128);
    for (int it = 0; it < K2_STAGES - 2; it++) {
      mbar_expect_tx(bar0 + 8 * it, 16384);
      tma_load_2d(smem_u32(sKV + it * 16384), &tmQKV, 0, (32 + head) * SEQ + it * 128, bar0 + 8 * it);
      tma_load_2d(smem_u32(sKV + it * 16384 + 8192), &tmQKV, 0, (64 + head) * SEQ + it * 128, bar0 + 8 * it);
    }
  }
  const int wg = tid >> 7, lane = tid & 31;
  const float c = 0.22360679774997896f * 1.4426950408889634f;
  float o[12];
#pragma unroll
  for (int i = 0; i < 12; i++) o[i] = 0.f;
  float m0 = -INFINITY, m1 = -INFINITY;
  const uint32_t qBase = smem_u32(sQ) + wg * 4096;
  mbar_wait(bar0 + 128, 0);
  float sa[32], sb[32];
  auto issue_qk = [&](float (&sc)[32], int hs) {
    const int it = hs >> 1, s = it % K2_STAGES;
    if ((hs & 1) == 0) mbar_wait(bar0 + 8 * s, (it / K2_STAGES) & 1);
    const uint32_t kBase = smem_u32(sKV + s * 16384) + (hs & 1) * 4096;
    wg_fence();
#pragma unroll
    for (int kk = 0; kk < 2; kk++)
      wgmma_ss_n64<0>(sc, make_desc(qBase + kk * 32, 16, 512, 2), make_desc(kBase + kk * 32, 16, 512, 2), kk);
    wg_commit();
  };
  auto soft_pv = [&](float (&sc)[32], int hs) {
    const int it = hs >> 1, s = it % K2_STAGES;
    const uint32_t vBase = smem_u32(sKV + s * 16384) + 8192 + (hs & 1) * 4096;

    reg_fence(sc); reg_fence(o);
    float mx0 = m0, mx1 = m1;
#pragma unroll
    for (int i = 0; i < 8; i++) {
      mx0 = fmaxf(mx0, fmaxf(sc[4 * i], sc[4 * i + 1]));
      mx1 = fmaxf(mx1, fmaxf(sc[4 * i + 2], sc[4 * i + 3]));
    }
    mx0 = fmaxf(mx0, __shfl_xor_sync(0xffffffffu, mx0, 1)); mx0 = fmaxf(mx0, __shfl_xor_sync(0xffffffffu, mx0, 2));
    mx1 = fmaxf(mx1, __shfl_xor_sync(0xffffffffu, mx1, 1)); mx1 = fmaxf(mx1, __shfl_xor_sync(0xffffffffu, mx1, 2));
    const float a0 = ex2((m0 - mx0) * c), a1 = ex2((m1 - mx1) * c);
    m0 = mx0; m1 = mx1;
    const float nb0 = -mx0 * c, nb1 = -mx1 * c;
    uint32_t p[16];
#pragma unroll
    for (int i = 0; i < 8; i++) {
      p[2 * i] = pack_bf16(ex2(fmaf(sc[4 * i], c, nb0)), ex2(fmaf(sc[4 * i + 1], c, nb0)));
      p[2 * i + 1] = pack_bf16(ex2(fmaf(sc[4 * i + 2], c, nb1)), ex2(fmaf(sc[4 * i + 3], c, nb1)));
    }
#pragma unroll
    for (int i = 0; i < 3; i++) { o[4 * i] *= a0; o[4 * i + 1] *= a0; o[4 * i + 2] *= a1; o[4 * i + 3] *= a1; }
    wg_fence();
#pragma unroll
    for (int kk = 0; kk < 4; kk++)
      wgmma_rs_n24<1>(o, p[4 * kk], p[4 * kk + 1], p[4 * kk + 2], p[4 * kk + 3], make_desc(vBase + kk * 1024, 16, 512, 2), 1);
    wg_commit();
  };
  issue_qk(sa, 0);
  for (int it = 0; it < 16; it++) {
    if (tid == 0 && it + K2_STAGES - 2 < 16) {
      const int n = it + K2_STAGES - 2, ns = n % K2_STAGES;
      mbar_wait(bar0 + 64 + 8 * ns, ((n / K2_STAGES) & 1) ^ 1);
      mbar_expect_tx(bar0 + 8 * ns, 16384);
      tma_load_2d(smem_u32(sKV + ns * 16384), &tmQKV, 0, (32 + head) * SEQ + n * 128, bar0 + 8 * ns);
      tma_load_2d(smem_u32(sKV + ns * 16384 + 8192), &tmQKV, 0, (64 + head) * SEQ + n * 128, bar0 + 8 * ns);
    }
    __syncwarp();
    issue_qk(sb, 2 * it + 1);
    wg_wait<1>();
    if (it > 0 && (tid & 127) == 0) mbar_arrive(bar0 + 64 + 8 * ((it - 1) % K2_STAGES));
    soft_pv(sa, 2 * it);
    if (it < 15) { issue_qk(sa, 2 * it + 2); wg_wait<1>(); } else { wg_wait<0>(); }
    soft_pv(sb, 2 * it + 1);
  }
  wg_wait<0>();
  reg_fence(o);
  const float l0 = __shfl_sync(0xffffffffu, o[8], (lane & ~3) | 2);
  const float l1 = __shfl_sync(0xffffffffu, o[10], (lane & ~3) | 2);
  const float i0 = 1.0f / l0, i1 = 1.0f / l1;
  const int q = lane & 3;
  const int row = qblk * 256 + wg * 64 + ((tid & 127) >> 5) * 16 + (lane >> 2);
#pragma unroll
  for (int i = 0; i < 3; i++) {
    const int d = 8 * i + 2 * q;
    if (d < 20) {
      *reinterpret_cast<uint32_t*>(g_o + (size_t)row * DM + head * 20 + d) = pack_bf16(o[4 * i] * i0, o[4 * i + 1] * i0);
      *reinterpret_cast<uint32_t*>(g_o + (size_t)(row + 8) * DM + head * 20 + d) = pack_bf16(o[4 * i + 2] * i1, o[4 * i + 3] * i1);
    }
  }
}

constexpr int G_STAGES = 6;
constexpr int G_STAGE_BYTES = 16384 + 16384;
constexpr int G_SMEM = G_STAGES * G_STAGE_BYTES + 1024;
template <int KTOT>
__global__ void __launch_bounds__(288, 1) k_gemm_res(const __grid_constant__ CUtensorMap tmA, const __grid_constant__ CUtensorMap tmB,
                                                     const bf16* __restrict__ res, bf16* __restrict__ out) {
  extern __shared__ __align__(1024) uint8_t smem[];
  const uint32_t bar0 = smem_u32(smem + G_STAGES * G_STAGE_BYTES);
  const int tid = threadIdx.x;
  const int mblk = blockIdx.x >> 3, nblk = blockIdx.x & 7;
  constexpr int NIT = KTOT / 64;
  if (tid == 0) {
    for (int s = 0; s < G_STAGES; s++) { mbar_init(bar0 + 8 * s, 1); mbar_init(bar0 + 64 + 8 * s, 2); }
    asm volatile("fence.mbarrier_init.release.cluster;" ::: "memory");
  }
  __syncthreads();
  if (tid >= 256) {
    if (tid == 256) {
      for (int it = 0; it < NIT; it++) {
        const int s = it % G_STAGES;
        mbar_wait(bar0 + 64 + 8 * s, ((it / G_STAGES) & 1) ^ 1);
        mbar_expect_tx(bar0 + 8 * s, G_STAGE_BYTES);
        const uint32_t st = smem_u32(smem + s * G_STAGE_BYTES);
        tma_load_2d(st, &tmA, it * 64, mblk * 128, bar0 + 8 * s);
        tma_load_2d(st + 16384, &tmB, nblk * 80, it * 64, bar0 + 8 * s);
        tma_load_2d(st + 16384 + 8192, &tmB, nblk * 80 + 64, it * 64, bar0 + 8 * s);
      }
    }
    return;
  }
  const int wg = tid >> 7;
  float acc[40];
#pragma unroll
  for (int i = 0; i < 40; i++) acc[i] = 0.f;
  for (int it = 0; it < NIT; it++) {
    const int s = it % G_STAGES;
    const uint32_t st = smem_u32(smem + s * G_STAGE_BYTES);
    mbar_wait(bar0 + 8 * s, (it / G_STAGES) & 1);
    wg_fence();
#pragma unroll
    for (int kk = 0; kk < 4; kk++) {
      uint64_t da = make_desc(st + wg * 8192 + kk * 32, 16, 1024, 1);
      uint64_t db = make_desc(st + 16384 + kk * 2048, 8192, 1024, 1);
      wgmma_ss_n80<1>(acc, da, db, 1);
    }
    wg_commit();
    wg_wait<1>();
    if (it > 0 && (tid & 127) == 0) mbar_arrive(bar0 + 64 + 8 * ((it - 1) % G_STAGES));
  }
  wg_wait<0>();
  reg_fence(acc);
  const int lane = tid & 31, q = lane & 3;
  const int row = mblk * 128 + wg * 64 + ((tid & 127) >> 5) * 16 + (lane >> 2);
#pragma unroll
  for (int i = 0; i < 10; i++) {
    const int col = nblk * 80 + 8 * i + 2 * q;
    const uint32_t r0 = *reinterpret_cast<const uint32_t*>(res + (size_t)row * DM + col);
    const uint32_t r1 = *reinterpret_cast<const uint32_t*>(res + (size_t)(row + 8) * DM + col);
    *reinterpret_cast<uint32_t*>(out + (size_t)row * DM + col) =
        pack_bf16(acc[4 * i] + __uint_as_float(r0 << 16), acc[4 * i + 1] + __uint_as_float(r0 & 0xffff0000u));
    *reinterpret_cast<uint32_t*>(out + (size_t)(row + 8) * DM + col) =
        pack_bf16(acc[4 * i + 2] + __uint_as_float(r1 << 16), acc[4 * i + 3] + __uint_as_float(r1 & 0xffff0000u));
  }
}

constexpr int K4_STAGES = 4;
constexpr int K4_SMEM = 163840 + K4_STAGES * 16384 + 1024;
__global__ void __launch_bounds__(288, 1) k4_ln_ffn(const __grid_constant__ CUtensorMap tmG, const __grid_constant__ CUtensorMap tmU) {
  extern __shared__ __align__(1024) uint8_t smem[];
  uint8_t* sA = smem;
  uint8_t* sB = smem + 163840;
  const uint32_t bar0 = smem_u32(smem + 163840 + K4_STAGES * 16384);
  const int tid = threadIdx.x;
  const int mblk = blockIdx.x >> 3, nblk = blockIdx.x & 7;
  if (tid == 0) {
    for (int s = 0; s < K4_STAGES; s++) { mbar_init(bar0 + 8 * s, 1); mbar_init(bar0 + 64 + 8 * s, 2); }
    asm volatile("fence.mbarrier_init.release.cluster;" ::: "memory");
  }
  __syncthreads();
  if (tid >= 256) {
    if (tid == 256) {
      for (int it = 0; it < 30; it++) {
        const int s = it % K4_STAGES;
        const int pass = it / 10, kb = it % 10;
        mbar_wait(bar0 + 64 + 8 * s, ((it / K4_STAGES) & 1) ^ 1);
        mbar_expect_tx(bar0 + 8 * s, 16384);
        tma_load_2d(smem_u32(sB + s * 16384), &tmG, nblk * 192 + pass * 64, kb * 64, bar0 + 8 * s);
        tma_load_2d(smem_u32(sB + s * 16384 + 8192), &tmU, nblk * 192 + pass * 64, kb * 64, bar0 + 8 * s);
      }
    }
    return;
  }
  ln_prologue(g_h, mblk * 128, sA, tid);
  fence_async_smem();
  named_bar_sync(1, 256);
  const int wg = tid >> 7;
  const uint32_t aBase = smem_u32(sA) + wg * 64 * 128;
  const uint32_t bBase = smem_u32(sB);
  const int lane = tid & 31, q = lane & 3;
  const int row = mblk * 128 + wg * 64 + ((tid & 127) >> 5) * 16 + (lane >> 2);
  for (int pass = 0; pass < 3; pass++) {
    float acc[64];
#pragma unroll
    for (int i = 0; i < 64; i++) acc[i] = 0.f;
    for (int kb = 0; kb < 10; kb++) {
      const int it = pass * 10 + kb;
      const int s = it % K4_STAGES;
      mbar_wait(bar0 + 8 * s, (it / K4_STAGES) & 1);
      wg_fence();
#pragma unroll
      for (int kk = 0; kk < 4; kk++) {
        uint64_t da = make_desc(aBase + kb * 16384 + kk * 32, 16, 1024, 1);
        uint64_t db = make_desc(bBase + s * 16384 + kk * 2048, 8192, 1024, 1);
        wgmma_ss_n128<1>(acc, da, db, 1);
      }
      wg_commit();
      wg_wait<1>();
      if (kb > 0 && (tid & 127) == 0) mbar_arrive(bar0 + 64 + 8 * ((it - 1) % K4_STAGES));
    }
    wg_wait<0>();
    if ((tid & 127) == 0) mbar_arrive(bar0 + 64 + 8 * ((pass * 10 + 9) % K4_STAGES));
    reg_fence(acc);
#pragma unroll
    for (int i = 0; i < 8; i++) {
      const int col = nblk * 192 + pass * 64 + 8 * i + 2 * q;
      float r[4];
#pragma unroll
      for (int j = 0; j < 4; j++) {
        const float g = acc[4 * i + j], u = acc[32 + 4 * i + j];
        r[j] = g / (1.0f + __expf(-g)) * u;
      }
      *reinterpret_cast<uint32_t*>(g_act + (size_t)row * FF + col) = pack_bf16(r[0], r[1]);
      *reinterpret_cast<uint32_t*>(g_act + (size_t)(row + 8) * FF + col) = pack_bf16(r[2], r[3]);
    }
  }
}

typedef CUresult (*EncodeFn)(CUtensorMap*, CUtensorMapDataType, cuuint32_t, void*, const cuuint64_t*, const cuuint64_t*,
                             const cuuint32_t*, const cuuint32_t*, CUtensorMapInterleave, CUtensorMapSwizzle,
                             CUtensorMapL2promotion, CUtensorMapFloatOOBfill);
static void make_map(EncodeFn fn, CUtensorMap* m, const void* ptr, uint64_t cols, uint64_t rows, uint32_t bc, uint32_t br,
                     CUtensorMapSwizzle sw) {
  cuuint64_t dims[2] = {cols, rows};
  cuuint64_t strides[1] = {cols * 2};
  cuuint32_t box[2] = {bc, br};
  cuuint32_t es[2] = {1, 1};
  fn(m, CU_TENSOR_MAP_DATA_TYPE_BFLOAT16, 2, const_cast<void*>(ptr), dims, strides, box, es, CU_TENSOR_MAP_INTERLEAVE_NONE, sw,
     CU_TENSOR_MAP_L2_PROMOTION_L2_128B, CU_TENSOR_MAP_FLOAT_OOB_FILL_NONE);
}

extern "C" void kernel_launch(void* const* d_in, const int* in_sizes, int n_in, void* d_out, int out_size) {
  const bf16* x = (const bf16*)d_in[0];
  const bf16* wqkv = (const bf16*)d_in[1];
  const bf16* wo = (const bf16*)d_in[2];
  const bf16* wg = (const bf16*)d_in[4];
  const bf16* wu = (const bf16*)d_in[5];
  const bf16* wd = (const bf16*)d_in[6];
  bf16* out = (bf16*)d_out;
  static EncodeFn fn = nullptr;
  static void *p_qkv, *p_o, *p_h, *p_act;
  if (!fn) {
    void* f = nullptr;
    cudaDriverEntryPointQueryResult qr;
    cudaGetDriverEntryPoint("cuTensorMapEncodeTiled", &f, cudaEnableDefault, &qr);
    fn = (EncodeFn)f;
    cudaGetSymbolAddress(&p_qkv, g_qkv);
    cudaGetSymbolAddress(&p_o, g_o);
    cudaGetSymbolAddress(&p_h, g_h);
    cudaGetSymbolAddress(&p_act, g_act);
    cudaFuncSetAttribute(k1_ln_qkv, cudaFuncAttributeMaxDynamicSharedMemorySize, K1_SMEM);
    cudaFuncSetAttribute(k2_attn, cudaFuncAttributeMaxDynamicSharedMemorySize, K2_SMEM);
    cudaFuncSetAttribute(k_gemm_res<640>, cudaFuncAttributeMaxDynamicSharedMemorySize, G_SMEM);
    cudaFuncSetAttribute(k_gemm_res<1536>, cudaFuncAttributeMaxDynamicSharedMemorySize, G_SMEM);
    cudaFuncSetAttribute(k4_ln_ffn, cudaFuncAttributeMaxDynamicSharedMemorySize, K4_SMEM);
  }
  CUtensorMap mWqkv, mQKV, mO, mWo, mWg, mWu, mAct, mWd;
  make_map(fn, &mWqkv, wqkv, 3 * DM, DM, 64, 32, CU_TENSOR_MAP_SWIZZLE_128B);
  make_map(fn, &mQKV, p_qkv, 32, 3 * NH * SEQ, 32, 128, CU_TENSOR_MAP_SWIZZLE_64B);
  make_map(fn, &mO, p_o, DM, SEQ, 64, 128, CU_TENSOR_MAP_SWIZZLE_128B);
  make_map(fn, &mWo, wo, DM, DM, 64, 64, CU_TENSOR_MAP_SWIZZLE_128B);
  make_map(fn, &mWg, wg, FF, DM, 64, 64, CU_TENSOR_MAP_SWIZZLE_128B);
  make_map(fn, &mWu, wu, FF, DM, 64, 64, CU_TENSOR_MAP_SWIZZLE_128B);
  make_map(fn, &mAct, p_act, FF, SEQ, 64, 128, CU_TENSOR_MAP_SWIZZLE_128B);
  make_map(fn, &mWd, wd, DM, FF, 64, 64, CU_TENSOR_MAP_SWIZZLE_128B);
  k1_ln_qkv<<<128, 288, K1_SMEM>>>(x, mWqkv);
  k2_attn<<<256, 512, K2_SMEM>>>(mQKV);
  k_gemm_res<640><<<128, 288, G_SMEM>>>(mO, mWo, x, (bf16*)p_h);
  k4_ln_ffn<<<128, 288, K4_SMEM>>>(mWg, mWu);
  k_gemm_res<1536><<<128, 288, G_SMEM>>>(mAct, mWd, (const bf16*)p_h, out);
}
```
